```python
import torch

def _softmax(x, axis=-1):
    return torch.softmax(x, dim=axis)

def _gelu(x):
    return torch.nn.functional.gelu(x, approximate='tanh')

def _silu(x):
    return torch.nn.functional.silu(x)

def _sigmoid(x):
    return torch.sigmoid(x)

def _layernorm(x, axis=-1, eps=1e-05):
    m = x.mean(dim=axis, keepdim=True)
    v = x.var(dim=axis, keepdim=True, unbiased=False)
    return (x - m) / torch.sqrt(v + eps)

def _scatter_add(tgt, idx, src, axis=0):
    return tgt.clone().index_add_(axis, idx, src)

def _segment_sum(src, seg, n):
    out = torch.zeros((n,) + src.shape[1:], dtype=src.dtype)
    return out.index_add_(0, seg, src)

def _pad(x, pw):
    flat = tuple((v for pair in reversed(pw) for v in pair))
    return torch.nn.functional.pad(x, flat)
kernel_name = 'standalone__video_videomae__vision'

def setup_inputs():

    _w = lambda a: (lambda t: t.to(torch.bfloat16) if t.is_floating_point() else t)(torch.as_tensor(a))
    T = 4
    N = 256
    C = max(384 // 4 * 4, 8)
    sc = C ** (-0.5)
    return {'x': _w((lambda *s: torch.randn(*s, dtype=torch.bfloat16) * 1.6)(1, T, N, C)), 'w_qkv_t': _w((lambda *s: torch.randn(*s, dtype=torch.bfloat16) * 1.6)(C, 3 * C) * sc), 'w_proj_t': _w((lambda *s: torch.randn(*s, dtype=torch.bfloat16) * 1.6)(C, C) * sc), 'w_qkv_s': _w((lambda *s: torch.randn(*s, dtype=torch.bfloat16) * 1.6)(C, 3 * C) * sc), 'w_proj_s': _w((lambda *s: torch.randn(*s, dtype=torch.bfloat16) * 0.8)(C, C) * sc), 'w1': _w((lambda *s: torch.randn(*s, dtype=torch.bfloat16) * 0.8)(C, 4 * C) * sc), 'w2': _w((lambda *s: torch.randn(*s, dtype=torch.bfloat16) * 0.8)(4 * C, C) * sc)}

def reference(x, w_qkv_t, w_proj_t, w_qkv_s, w_proj_s, w1, w2):
    B, T, N, C = x.shape
    Hd = 4
    D = C // Hd
    scale = D ** (-0.5)
    h = _layernorm(x, axis=-1)
    qkv = torch.einsum('btnc,ce->btne', h, w_qkv_t).reshape(B, T, N, 3, Hd, D)
    q = qkv[:, :, :, 0, :, :].clone()
    k = qkv[:, :, :, 1, :, :].clone()
    v = qkv[:, :, :, 2, :, :].clone()
    a = torch.einsum('btnhd,bsnhd->bnhts', q, k) * scale
    a = _softmax(a, axis=-1)
    o = torch.einsum('bnhts,bsnhd->btnhd', a, v).reshape(B, T, N, C)
    x = x + torch.einsum('btnc,ce->btne', o, w_proj_t)
    h = _layernorm(x, axis=-1)
    qkv = torch.einsum('btnc,ce->btne', h, w_qkv_s).reshape(B, T, N, 3, Hd, D)
    q = qkv[:, :, :, 0, :, :].clone()
    k = qkv[:, :, :, 1, :, :].clone()
    v = qkv[:, :, :, 2, :, :].clone()
    a = torch.einsum('btnhd,btmhd->bthnm', q, k) * scale
    a = _softmax(a, axis=-1)
    o = torch.einsum('bthnm,btmhd->btnhd', a, v).reshape(B, T, N, C)
    x = x + torch.einsum('btnc,ce->btne', o, w_proj_s)
    h = _layernorm(x, axis=-1)
    return x + _gelu(h @ w1) @ w2
```

```cpp
#include <cuda_runtime.h>
#include <cuda_bf16.h>
#include <cuda.h>
#include <stdint.h>

namespace {

constexpr int CS = 6;
constexpr int NCL = 16;
constexpr int NTHREADS = 384;

constexpr uint32_t SM_A0 = 0;
constexpr uint32_t SM_A1 = 49152;
constexpr uint32_t SM_RING = 98304;
constexpr uint32_t SLOT = 16384;
constexpr int NSLOT = 6;
constexpr uint32_t SM_STG = 196608;
constexpr uint32_t SM_RES = 212992;
constexpr uint32_t SM_SC = 221184;
constexpr uint32_t SM_ST = 227328;
constexpr uint32_t SM_ML = 230912;
constexpr uint32_t SM_BAR = 231936;
constexpr uint32_t SM_EPOCH = SM_BAR + 448;
constexpr uint32_t SM_TOTAL = 232448;

enum {
    B_FULL = 0, B_EMPTY = 6, B_X = 12, B_SC, B_OT, B_X1, B_ST2, B_A0FREE, B_X1P, B_QDONE,
    B_K0, B_K1, B_V0, B_V1, B_KFREE, B_OS, B_X2, B_ST3, B_LAND, B_PART, B_DONE, B_X1ST, B_KVST, B_STGFREE, B_VW, B_VFREE, B_A1FREE, B_W1X, B_KVISS, B_COUNT
};

struct Params {
    CUtensorMap tm_x;
    CUtensorMap tm_x1s;
    CUtensorMap tm_x1l;
    CUtensorMap tm_kvs;
    CUtensorMap tm_kvl;
    CUtensorMap tm_out;
    CUtensorMap tm_w[6];
    const void* wptr[6];
    uint32_t stage[6][54];
};

__device__ __align__(1024) uint8_t g_x1[1024 * 384 * 2];
__device__ __align__(1024) uint8_t g_kv[1024 * 768 * 2];
__device__ __align__(1024) uint8_t g_ot[NCL * CS * 8192];
__device__ __align__(1024) uint8_t g_x1i[NCL * CS * 8192];
__device__ __align__(1024) uint8_t g_os[NCL * 4 * 12288];
__device__ __align__(1024) uint8_t g_x2i[NCL * CS * 8192];
__device__ float2 g_part[1024 * 6];
__device__ __align__(128) unsigned g_cnt[5 * 32];
__device__ unsigned g_epoch;

__device__ __forceinline__ uint32_t smem_u32(const void* p) { return (uint32_t)__cvta_generic_to_shared(p); }
__device__ __forceinline__ void mbar_init(uint32_t bar, uint32_t cnt) { asm volatile("mbarrier.init.shared::cta.b64 [%0], %1;" :: "r"(bar), "r"(cnt) : "memory"); }
__device__ __forceinline__ void mbar_expect_tx(uint32_t bar, uint32_t bytes) { asm volatile("mbarrier.arrive.expect_tx.shared::cta.b64 _, [%0], %1;" :: "r"(bar), "r"(bytes) : "memory"); }
__device__ __forceinline__ void mbar_arrive(uint32_t bar) { asm volatile("mbarrier.arrive.shared::cta.b64 _, [%0];" :: "r"(bar) : "memory"); }
__device__ __forceinline__ void mbar_arrive_remote(uint32_t bar_cluster) { asm volatile("mbarrier.arrive.shared::cluster.b64 _, [%0];" :: "r"(bar_cluster) : "memory"); }
__device__ __forceinline__ uint32_t mbar_try(uint32_t bar, uint32_t parity) {
    uint32_t done;
    asm volatile("{\n.reg .pred p;\nmbarrier.try_wait.parity.shared::cta.b64 p, [%1], %2;\nselp.u32 %0, 1, 0, p;\n}" : "=r"(done) : "r"(bar), "r"(parity) : "memory");
    return done;
}
__device__ __forceinline__ uint32_t mbar_try_cl(uint32_t bar, uint32_t parity) {
    uint32_t done;
    asm volatile("{\n.reg .pred p;\nmbarrier.try_wait.parity.acquire.cluster.shared::cta.b64 p, [%1], %2;\nselp.u32 %0, 1, 0, p;\n}" : "=r"(done) : "r"(bar), "r"(parity) : "memory");
    return done;
}
__device__ __forceinline__ void mbar_wait(uint32_t bar, uint32_t parity) { while (!mbar_try(bar, parity)) {} }
__device__ __forceinline__ void mbar_wait_cl(uint32_t bar, uint32_t parity) { while (!mbar_try_cl(bar, parity)) {} }
__device__ __forceinline__ unsigned long long gtime() { unsigned long long t; asm volatile("mov.u64 %0, %%globaltimer;" : "=l"(t)); return t; }
constexpr unsigned long long TIMEOUT_NS = 500000000ull;
__device__ __forceinline__ void mbar_wait_trap(uint32_t bar, uint32_t parity) {
    if (mbar_try(bar, parity)) return;
    const unsigned long long t0 = gtime();
    while (!mbar_try(bar, parity)) { if (gtime() - t0 > TIMEOUT_NS) __trap(); }
}
__device__ __forceinline__ uint32_t mapa(uint32_t a, uint32_t r) { uint32_t o; asm("mapa.shared::cluster.u32 %0, %1, %2;" : "=r"(o) : "r"(a), "r"(r)); return o; }
__device__ __forceinline__ bool elect_one() {
    uint32_t pred;
    asm volatile("{\n.reg .pred p;\nelect.sync _|p, 0xffffffff;\nselp.u32 %0, 1, 0, p;\n}" : "=r"(pred));
    return pred != 0;
}
__device__ __forceinline__ void bar_sync(int id, int n) { asm volatile("bar.sync %0, %1;" :: "r"(id), "r"(n) : "memory"); }
__device__ __forceinline__ void bar_arrive(int id, int n) { asm volatile("bar.arrive %0, %1;" :: "r"(id), "r"(n) : "memory"); }
__device__ __forceinline__ void fence_async_smem() { asm volatile("fence.proxy.async.shared::cta;" ::: "memory"); }
__device__ __forceinline__ void fence_async_all() { asm volatile("fence.proxy.async;" ::: "memory"); }
__device__ __forceinline__ void tma_ld2(uint32_t dst, const CUtensorMap* tm, int c0, int c1, uint32_t bar) {
    asm volatile("cp.async.bulk.tensor.2d.shared::cluster.global.mbarrier::complete_tx::bytes [%0], [%1, {%3, %4}], [%2];"
        :: "r"(dst), "l"(tm), "r"(bar), "r"(c0), "r"(c1) : "memory");
}
__device__ __forceinline__ void tma_ld3(uint32_t dst, const CUtensorMap* tm, int c0, int c1, int c2, uint32_t bar) {
    asm volatile("cp.async.bulk.tensor.3d.shared::cluster.global.mbarrier::complete_tx::bytes [%0], [%1, {%3, %4, %5}], [%2];"
        :: "r"(dst), "l"(tm), "r"(bar), "r"(c0), "r"(c1), "r"(c2) : "memory");
}
__device__ __forceinline__ void tma_ld5(uint32_t dst, const CUtensorMap* tm, int c0, int c1, int c2, int c3, int c4, uint32_t bar) {
    asm volatile("cp.async.bulk.tensor.5d.shared::cluster.global.mbarrier::complete_tx::bytes [%0], [%1, {%3, %4, %5, %6, %7}], [%2];"
        :: "r"(dst), "l"(tm), "r"(bar), "r"(c0), "r"(c1), "r"(c2), "r"(c3), "r"(c4) : "memory");
}
__device__ __forceinline__ void tma_st2(const CUtensorMap* tm, int c0, int c1, uint32_t src) {
    asm volatile("cp.async.bulk.tensor.2d.global.shared::cta.bulk_group [%0, {%2, %3}], [%1];"
        :: "l"(tm), "r"(src), "r"(c0), "r"(c1) : "memory");
}
__device__ __forceinline__ void tma_st5(const CUtensorMap* tm, int c0, int c1, int c2, int c3, int c4, uint32_t src) {
    asm volatile("cp.async.bulk.tensor.5d.global.shared::cta.bulk_group [%0, {%2, %3, %4, %5, %6}], [%1];"
        :: "l"(tm), "r"(src), "r"(c0), "r"(c1), "r"(c2), "r"(c3), "r"(c4) : "memory");
}
__device__ __forceinline__ void bulk_s2g(void* dst, uint32_t src, uint32_t bytes) {
    asm volatile("cp.async.bulk.global.shared::cta.bulk_group [%0], [%1], %2;" :: "l"(dst), "r"(src), "r"(bytes) : "memory");
}
__device__ __forceinline__ void bulk_g2s_mc(uint32_t dst, const void* src, uint32_t bytes, uint32_t bar, uint16_t mask) {
    asm volatile("cp.async.bulk.shared::cluster.global.mbarrier::complete_tx::bytes.multicast::cluster [%0], [%1], %2, [%3], %4;"
        :: "r"(dst), "l"(src), "r"(bytes), "r"(bar), "h"(mask) : "memory");
}
__device__ __forceinline__ void bulk_g2s(uint32_t dst, const void* src, uint32_t bytes, uint32_t bar) {
    asm volatile("cp.async.bulk.shared::cluster.global.mbarrier::complete_tx::bytes [%0], [%1], %2, [%3];" :: "r"(dst), "l"(src), "r"(bytes), "r"(bar) : "memory");
}
__device__ __forceinline__ void bulk_commit() { asm volatile("cp.async.bulk.commit_group;" ::: "memory"); }
template <int N> __device__ __forceinline__ void bulk_wait() { asm volatile("cp.async.bulk.wait_group %0;" :: "n"(N) : "memory"); }
template <int N> __device__ __forceinline__ void bulk_wait_read() { asm volatile("cp.async.bulk.wait_group.read %0;" :: "n"(N) : "memory"); }
__device__ __forceinline__ void bulk_prefetch(const void* src, uint32_t bytes) { asm volatile("cp.async.bulk.prefetch.L2.global [%0], %1;" :: "l"(src), "r"(bytes) : "memory"); }
__device__ __forceinline__ void st_async_v4(uint32_t dst, uint32_t a, uint32_t b, uint32_t c, uint32_t d, uint32_t bar) {
    asm volatile("st.async.shared::cluster.mbarrier::complete_tx::bytes.v4.b32 [%0], {%1, %2, %3, %4}, [%5];"
        :: "r"(dst), "r"(a), "r"(b), "r"(c), "r"(d), "r"(bar) : "memory");
}
__device__ __forceinline__ void st_async_v2(uint32_t dst, uint32_t a, uint32_t b, uint32_t bar) {
    asm volatile("st.async.shared::cluster.mbarrier::complete_tx::bytes.v2.b32 [%0], {%1, %2}, [%3];"
        :: "r"(dst), "r"(a), "r"(b), "r"(bar) : "memory");
}
__device__ __forceinline__ void ldsm4(uint32_t addr, uint32_t& r0, uint32_t& r1, uint32_t& r2, uint32_t& r3) {
    asm volatile("ldmatrix.sync.aligned.m8n8.x4.shared.b16 {%0, %1, %2, %3}, [%4];" : "=r"(r0), "=r"(r1), "=r"(r2), "=r"(r3) : "r"(addr) : "memory");
}
__device__ __forceinline__ void stsm4(uint32_t addr, uint32_t r0, uint32_t r1, uint32_t r2, uint32_t r3) {
    asm volatile("stmatrix.sync.aligned.m8n8.x4.shared.b16 [%0], {%1, %2, %3, %4};" :: "r"(addr), "r"(r0), "r"(r1), "r"(r2), "r"(r3) : "memory");
}
extern __shared__ __align__(1024) uint8_t smem[];
template <class T> __device__ __forceinline__ T& sm_at(uint32_t off) { return *reinterpret_cast<T*>(smem + off); }
__device__ __forceinline__ uint32_t pack_bf16(float lo, float hi) { uint32_t r; asm("cvt.rn.bf16x2.f32 %0, %1, %2;" : "=r"(r) : "f"(hi), "f"(lo)); return r; }
__device__ __forceinline__ float bf_lo(uint32_t v) { return __uint_as_float(v << 16); }
__device__ __forceinline__ float bf_hi(uint32_t v) { return __uint_as_float(v & 0xffff0000u); }
__device__ __forceinline__ float ex2(float x) { float y; asm("ex2.approx.ftz.f32 %0, %1;" : "=f"(y) : "f"(x)); return y; }
__device__ __forceinline__ float tanh_ap(float x) { float y; asm volatile("tanh.approx.f32 %0, %1;" : "=f"(y) : "f"(x)); return y; }
__device__ __forceinline__ float ex2v(float x) { float y; asm volatile("ex2.approx.ftz.f32 %0, %1;" : "=f"(y) : "f"(x)); return y; }
__device__ __forceinline__ void wg_fence() { asm volatile("wgmma.fence.sync.aligned;" ::: "memory"); }
__device__ __forceinline__ void wg_commit() { asm volatile("wgmma.commit_group.sync.aligned;" ::: "memory"); }
template <int N> __device__ __forceinline__ void wg_wait() { asm volatile("wgmma.wait_group.sync.aligned %0;" :: "n"(N) : "memory"); }
template <int N> __device__ __forceinline__ void pin_f(float (&d)[N]) {
#pragma unroll
    for (int i = 0; i < N; i++) asm volatile("" : "+f"(d[i]) :: "memory");
}
template <int N> __device__ __forceinline__ void pin_r(uint32_t (&d)[N]) {
#pragma unroll
    for (int i = 0; i < N; i++) asm volatile("" : "+r"(d[i]) :: "memory");
}
constexpr uint64_t DESC_128 = (1ull << 62), DESC_64 = (2ull << 62);
__device__ __forceinline__ uint64_t mk_desc(uint32_t addr, uint32_t lbo, uint32_t sbo, uint64_t swz) {
    return (uint64_t)((addr & 0x3FFFF) >> 4) | ((uint64_t)(lbo >> 4) << 16) | ((uint64_t)(sbo >> 4) << 32) | swz;
}

__device__ __forceinline__ void hadd2_v(uint32_t& a, uint32_t b) { asm volatile("add.rn.bf16x2 %0, %0, %1;" : "+r"(a) : "r"(b)); }
__device__ __forceinline__ uint32_t hadd2_bf(uint32_t a, uint32_t b) { uint32_t r; asm("add.rn.bf16x2 %0, %1, %2;" : "=r"(r) : "r"(a), "r"(b)); return r; }
__device__ __forceinline__ uint32_t movm(uint32_t a) { uint32_t r; asm volatile("movmatrix.sync.aligned.m8n8.trans.b16 %0, %1;" : "=r"(r) : "r"(a)); return r; }
__device__ __forceinline__ void mma16816(float (&d)[4], uint32_t a0, uint32_t a1, uint32_t a2, uint32_t a3, uint32_t b0, uint32_t b1) {
    asm volatile("mma.sync.aligned.m16n8k16.row.col.f32.bf16.bf16.f32 {%0, %1, %2, %3}, {%4, %5, %6, %7}, {%8, %9}, {%0, %1, %2, %3};"
        : "+f"(d[0]), "+f"(d[1]), "+f"(d[2]), "+f"(d[3]) : "r"(a0), "r"(a1), "r"(a2), "r"(a3), "r"(b0), "r"(b1));
}
__device__ __forceinline__ void mma16816p(float* d, uint32_t a0, uint32_t a1, uint32_t a2, uint32_t a3, uint32_t b0, uint32_t b1) {
    asm volatile("mma.sync.aligned.m16n8k16.row.col.f32.bf16.bf16.f32 {%0, %1, %2, %3}, {%4, %5, %6, %7}, {%8, %9}, {%0, %1, %2, %3};"
        : "+f"(d[0]), "+f"(d[1]), "+f"(d[2]), "+f"(d[3]) : "r"(a0), "r"(a1), "r"(a2), "r"(a3), "r"(b0), "r"(b1));
}
__device__ __forceinline__ void wgmma_rs_n128(float (&d)[64], uint32_t a0, uint32_t a1, uint32_t a2, uint32_t a3, uint64_t db, int sd) {
    asm volatile("{\n.reg .pred p;\nsetp.ne.b32 p, %69, 0;\n"
        "wgmma.mma_async.sync.aligned.m64n128k16.f32.bf16.bf16 {%0, %1, %2, %3, %4, %5, %6, %7, %8, %9, %10, %11, %12, %13, %14, %15, %16, %17, %18, %19, %20, %21, %22, %23, %24, %25, %26, %27, %28, %29, %30, %31, %32, %33, %34, %35, %36, %37, %38, %39, %40, %41, %42, %43, %44, %45, %46, %47, %48, %49, %50, %51, %52, %53, %54, %55, %56, %57, %58, %59, %60, %61, %62, %63}, {%64, %65, %66, %67}, %68, p, 1, 1, 1;\n}\n"
        : "+f"(d[0]), "+f"(d[1]), "+f"(d[2]), "+f"(d[3]), "+f"(d[4]), "+f"(d[5]), "+f"(d[6]), "+f"(d[7]), "+f"(d[8]), "+f"(d[9]), "+f"(d[10]), "+f"(d[11]), "+f"(d[12]), "+f"(d[13]), "+f"(d[14]), "+f"(d[15]), "+f"(d[16]), "+f"(d[17]), "+f"(d[18]), "+f"(d[19]), "+f"(d[20]), "+f"(d[21]), "+f"(d[22]), "+f"(d[23]), "+f"(d[24]), "+f"(d[25]), "+f"(d[26]), "+f"(d[27]), "+f"(d[28]), "+f"(d[29]), "+f"(d[30]), "+f"(d[31]), "+f"(d[32]), "+f"(d[33]), "+f"(d[34]), "+f"(d[35]), "+f"(d[36]), "+f"(d[37]), "+f"(d[38]), "+f"(d[39]), "+f"(d[40]), "+f"(d[41]), "+f"(d[42]), "+f"(d[43]), "+f"(d[44]), "+f"(d[45]), "+f"(d[46]), "+f"(d[47]), "+f"(d[48]), "+f"(d[49]), "+f"(d[50]), "+f"(d[51]), "+f"(d[52]), "+f"(d[53]), "+f"(d[54]), "+f"(d[55]), "+f"(d[56]), "+f"(d[57]), "+f"(d[58]), "+f"(d[59]), "+f"(d[60]), "+f"(d[61]), "+f"(d[62]), "+f"(d[63])
        : "r"(a0), "r"(a1), "r"(a2), "r"(a3), "l"(db), "r"(sd));
}

__device__ __forceinline__ void wgmma_rs_n96(float (&d)[48], uint32_t a0, uint32_t a1, uint32_t a2, uint32_t a3, uint64_t db, int sd) {
    asm volatile("{\n.reg .pred p;\nsetp.ne.b32 p, %53, 0;\n"
        "wgmma.mma_async.sync.aligned.m64n96k16.f32.bf16.bf16 {%0, %1, %2, %3, %4, %5, %6, %7, %8, %9, %10, %11, %12, %13, %14, %15, %16, %17, %18, %19, %20, %21, %22, %23, %24, %25, %26, %27, %28, %29, %30, %31, %32, %33, %34, %35, %36, %37, %38, %39, %40, %41, %42, %43, %44, %45, %46, %47}, {%48, %49, %50, %51}, %52, p, 1, 1, 1;\n}\n"
        : "+f"(d[0]), "+f"(d[1]), "+f"(d[2]), "+f"(d[3]), "+f"(d[4]), "+f"(d[5]), "+f"(d[6]), "+f"(d[7]), "+f"(d[8]), "+f"(d[9]), "+f"(d[10]), "+f"(d[11]), "+f"(d[12]), "+f"(d[13]), "+f"(d[14]), "+f"(d[15]), "+f"(d[16]), "+f"(d[17]), "+f"(d[18]), "+f"(d[19]), "+f"(d[20]), "+f"(d[21]), "+f"(d[22]), "+f"(d[23]), "+f"(d[24]), "+f"(d[25]), "+f"(d[26]), "+f"(d[27]), "+f"(d[28]), "+f"(d[29]), "+f"(d[30]), "+f"(d[31]), "+f"(d[32]), "+f"(d[33]), "+f"(d[34]), "+f"(d[35]), "+f"(d[36]), "+f"(d[37]), "+f"(d[38]), "+f"(d[39]), "+f"(d[40]), "+f"(d[41]), "+f"(d[42]), "+f"(d[43]), "+f"(d[44]), "+f"(d[45]), "+f"(d[46]), "+f"(d[47])
        : "r"(a0), "r"(a1), "r"(a2), "r"(a3), "l"(db), "r"(sd));
}

__device__ __forceinline__ void wgmma_rs_n64(float (&d)[32], uint32_t a0, uint32_t a1, uint32_t a2, uint32_t a3, uint64_t db, int sd) {
    asm volatile("{\n.reg .pred p;\nsetp.ne.b32 p, %37, 0;\n"
        "wgmma.mma_async.sync.aligned.m64n64k16.f32.bf16.bf16 {%0, %1, %2, %3, %4, %5, %6, %7, %8, %9, %10, %11, %12, %13, %14, %15, %16, %17, %18, %19, %20, %21, %22, %23, %24, %25, %26, %27, %28, %29, %30, %31}, {%32, %33, %34, %35}, %36, p, 1, 1, 1;\n}\n"
        : "+f"(d[0]), "+f"(d[1]), "+f"(d[2]), "+f"(d[3]), "+f"(d[4]), "+f"(d[5]), "+f"(d[6]), "+f"(d[7]), "+f"(d[8]), "+f"(d[9]), "+f"(d[10]), "+f"(d[11]), "+f"(d[12]), "+f"(d[13]), "+f"(d[14]), "+f"(d[15]), "+f"(d[16]), "+f"(d[17]), "+f"(d[18]), "+f"(d[19]), "+f"(d[20]), "+f"(d[21]), "+f"(d[22]), "+f"(d[23]), "+f"(d[24]), "+f"(d[25]), "+f"(d[26]), "+f"(d[27]), "+f"(d[28]), "+f"(d[29]), "+f"(d[30]), "+f"(d[31])
        : "r"(a0), "r"(a1), "r"(a2), "r"(a3), "l"(db), "r"(sd));
}

__device__ __forceinline__ void wgmma_ss_n64(float (&d)[32], uint64_t da, uint64_t db, int sd) {
    asm volatile("{\n.reg .pred p;\nsetp.ne.b32 p, %34, 0;\n"
        "wgmma.mma_async.sync.aligned.m64n64k16.f32.bf16.bf16 {%0, %1, %2, %3, %4, %5, %6, %7, %8, %9, %10, %11, %12, %13, %14, %15, %16, %17, %18, %19, %20, %21, %22, %23, %24, %25, %26, %27, %28, %29, %30, %31}, %32, %33, p, 1, 1, 0, 1;\n}\n"
        : "+f"(d[0]), "+f"(d[1]), "+f"(d[2]), "+f"(d[3]), "+f"(d[4]), "+f"(d[5]), "+f"(d[6]), "+f"(d[7]), "+f"(d[8]), "+f"(d[9]), "+f"(d[10]), "+f"(d[11]), "+f"(d[12]), "+f"(d[13]), "+f"(d[14]), "+f"(d[15]), "+f"(d[16]), "+f"(d[17]), "+f"(d[18]), "+f"(d[19]), "+f"(d[20]), "+f"(d[21]), "+f"(d[22]), "+f"(d[23]), "+f"(d[24]), "+f"(d[25]), "+f"(d[26]), "+f"(d[27]), "+f"(d[28]), "+f"(d[29]), "+f"(d[30]), "+f"(d[31])
        : "l"(da), "l"(db), "r"(sd));
}

__device__ __forceinline__ void wgmma_ss_n128_bn(float (&d)[64], uint64_t da, uint64_t db, int sd) {
    asm volatile("{\n.reg .pred p;\nsetp.ne.b32 p, %66, 0;\n"
        "wgmma.mma_async.sync.aligned.m64n128k16.f32.bf16.bf16 {%0, %1, %2, %3, %4, %5, %6, %7, %8, %9, %10, %11, %12, %13, %14, %15, %16, %17, %18, %19, %20, %21, %22, %23, %24, %25, %26, %27, %28, %29, %30, %31, %32, %33, %34, %35, %36, %37, %38, %39, %40, %41, %42, %43, %44, %45, %46, %47, %48, %49, %50, %51, %52, %53, %54, %55, %56, %57, %58, %59, %60, %61, %62, %63}, %64, %65, p, 1, 1, 0, 0;\n}\n"
        : "+f"(d[0]), "+f"(d[1]), "+f"(d[2]), "+f"(d[3]), "+f"(d[4]), "+f"(d[5]), "+f"(d[6]), "+f"(d[7]), "+f"(d[8]), "+f"(d[9]), "+f"(d[10]), "+f"(d[11]), "+f"(d[12]), "+f"(d[13]), "+f"(d[14]), "+f"(d[15]), "+f"(d[16]), "+f"(d[17]), "+f"(d[18]), "+f"(d[19]), "+f"(d[20]), "+f"(d[21]), "+f"(d[22]), "+f"(d[23]), "+f"(d[24]), "+f"(d[25]), "+f"(d[26]), "+f"(d[27]), "+f"(d[28]), "+f"(d[29]), "+f"(d[30]), "+f"(d[31]), "+f"(d[32]), "+f"(d[33]), "+f"(d[34]), "+f"(d[35]), "+f"(d[36]), "+f"(d[37]), "+f"(d[38]), "+f"(d[39]), "+f"(d[40]), "+f"(d[41]), "+f"(d[42]), "+f"(d[43]), "+f"(d[44]), "+f"(d[45]), "+f"(d[46]), "+f"(d[47]), "+f"(d[48]), "+f"(d[49]), "+f"(d[50]), "+f"(d[51]), "+f"(d[52]), "+f"(d[53]), "+f"(d[54]), "+f"(d[55]), "+f"(d[56]), "+f"(d[57]), "+f"(d[58]), "+f"(d[59]), "+f"(d[60]), "+f"(d[61]), "+f"(d[62]), "+f"(d[63])
        : "l"(da), "l"(db), "r"(sd));
}

__device__ __forceinline__ void wgmma_ss_n192(float (&d)[96], uint64_t da, uint64_t db, int sd) {
    asm volatile("{\n.reg .pred p;\nsetp.ne.b32 p, %98, 0;\n"
        "wgmma.mma_async.sync.aligned.m64n192k16.f32.bf16.bf16 {%0, %1, %2, %3, %4, %5, %6, %7, %8, %9, %10, %11, %12, %13, %14, %15, %16, %17, %18, %19, %20, %21, %22, %23, %24, %25, %26, %27, %28, %29, %30, %31, %32, %33, %34, %35, %36, %37, %38, %39, %40, %41, %42, %43, %44, %45, %46, %47, %48, %49, %50, %51, %52, %53, %54, %55, %56, %57, %58, %59, %60, %61, %62, %63, %64, %65, %66, %67, %68, %69, %70, %71, %72, %73, %74, %75, %76, %77, %78, %79, %80, %81, %82, %83, %84, %85, %86, %87, %88, %89, %90, %91, %92, %93, %94, %95}, %96, %97, p, 1, 1, 0, 1;\n}\n"
        : "+f"(d[0]), "+f"(d[1]), "+f"(d[2]), "+f"(d[3]), "+f"(d[4]), "+f"(d[5]), "+f"(d[6]), "+f"(d[7]), "+f"(d[8]), "+f"(d[9]), "+f"(d[10]), "+f"(d[11]), "+f"(d[12]), "+f"(d[13]), "+f"(d[14]), "+f"(d[15]), "+f"(d[16]), "+f"(d[17]), "+f"(d[18]), "+f"(d[19]), "+f"(d[20]), "+f"(d[21]), "+f"(d[22]), "+f"(d[23]), "+f"(d[24]), "+f"(d[25]), "+f"(d[26]), "+f"(d[27]), "+f"(d[28]), "+f"(d[29]), "+f"(d[30]), "+f"(d[31]), "+f"(d[32]), "+f"(d[33]), "+f"(d[34]), "+f"(d[35]), "+f"(d[36]), "+f"(d[37]), "+f"(d[38]), "+f"(d[39]), "+f"(d[40]), "+f"(d[41]), "+f"(d[42]), "+f"(d[43]), "+f"(d[44]), "+f"(d[45]), "+f"(d[46]), "+f"(d[47]), "+f"(d[48]), "+f"(d[49]), "+f"(d[50]), "+f"(d[51]), "+f"(d[52]), "+f"(d[53]), "+f"(d[54]), "+f"(d[55]), "+f"(d[56]), "+f"(d[57]), "+f"(d[58]), "+f"(d[59]), "+f"(d[60]), "+f"(d[61]), "+f"(d[62]), "+f"(d[63]), "+f"(d[64]), "+f"(d[65]), "+f"(d[66]), "+f"(d[67]), "+f"(d[68]), "+f"(d[69]), "+f"(d[70]), "+f"(d[71]), "+f"(d[72]), "+f"(d[73]), "+f"(d[74]), "+f"(d[75]), "+f"(d[76]), "+f"(d[77]), "+f"(d[78]), "+f"(d[79]), "+f"(d[80]), "+f"(d[81]), "+f"(d[82]), "+f"(d[83]), "+f"(d[84]), "+f"(d[85]), "+f"(d[86]), "+f"(d[87]), "+f"(d[88]), "+f"(d[89]), "+f"(d[90]), "+f"(d[91]), "+f"(d[92]), "+f"(d[93]), "+f"(d[94]), "+f"(d[95])
        : "l"(da), "l"(db), "r"(sd));
}

template <int OFF> __device__ __forceinline__ void wgmma_ss_n64_off(float (&d)[96], uint64_t da, uint64_t db, int sd) {
    asm volatile("{\n.reg .pred p;\nsetp.ne.b32 p, %34, 0;\n"
        "wgmma.mma_async.sync.aligned.m64n64k16.f32.bf16.bf16 {%0, %1, %2, %3, %4, %5, %6, %7, %8, %9, %10, %11, %12, %13, %14, %15, %16, %17, %18, %19, %20, %21, %22, %23, %24, %25, %26, %27, %28, %29, %30, %31}, %32, %33, p, 1, 1, 0, 1;\n}\n"
        : "+f"(d[OFF + 0]), "+f"(d[OFF + 1]), "+f"(d[OFF + 2]), "+f"(d[OFF + 3]), "+f"(d[OFF + 4]), "+f"(d[OFF + 5]), "+f"(d[OFF + 6]), "+f"(d[OFF + 7]), "+f"(d[OFF + 8]), "+f"(d[OFF + 9]), "+f"(d[OFF + 10]), "+f"(d[OFF + 11]), "+f"(d[OFF + 12]), "+f"(d[OFF + 13]), "+f"(d[OFF + 14]), "+f"(d[OFF + 15]), "+f"(d[OFF + 16]), "+f"(d[OFF + 17]), "+f"(d[OFF + 18]), "+f"(d[OFF + 19]), "+f"(d[OFF + 20]), "+f"(d[OFF + 21]), "+f"(d[OFF + 22]), "+f"(d[OFF + 23]), "+f"(d[OFF + 24]), "+f"(d[OFF + 25]), "+f"(d[OFF + 26]), "+f"(d[OFF + 27]), "+f"(d[OFF + 28]), "+f"(d[OFF + 29]), "+f"(d[OFF + 30]), "+f"(d[OFF + 31])
        : "l"(da), "l"(db), "r"(sd));
}

#define STAMP(wg, ev) do {} while (0)
#define STAMP1(wg, ev) do {} while (0)
#define SIG_MODE 2

__device__ __forceinline__ constexpr uint32_t bar_count(int i) {
    return ((i >= B_EMPTY && i < B_EMPTY + 6) || i == B_A0FREE || i == B_QDONE || i == B_X1ST || i == B_KVST || i == B_A1FREE) ? 4
         : (i == B_X1 || i == B_X2) ? 5 : i == B_KFREE ? 48 : i == B_LAND ? 20 : i == B_DONE ? 8 : i == B_VFREE ? 24 : 1;
}
__device__ __forceinline__ constexpr uint32_t bar_tx(int i) {
    return i == B_SC ? 6144 : (i == B_OT || i == B_OS) ? 49152 : (i == B_X1 || i == B_X2 || i == B_PART) ? 40960 : (i == B_ST2 || i == B_ST3) ? 3072 : 0;
}
__device__ __forceinline__ uint32_t bar_addr(uint32_t sb, int b) { return sb + SM_BAR + b * 8; }

struct RingPos { uint32_t slot, par; };
__device__ __forceinline__ RingPos ring_pos(uint32_t s) { const uint32_t q = (s * 43u) >> 8; RingPos r; r.slot = s - 6u * q; r.par = q & 1u; return r; }
__device__ __forceinline__ void ring_adv(RingPos& r, uint32_t stride) { r.slot += stride; if (r.slot >= 6u) { r.slot -= 6u; r.par ^= 1u; } }
__device__ __forceinline__ void ring_release(uint32_t sb, uint32_t slot, int lane) { if (lane == 0) mbar_arrive(sb + SM_BAR + (B_EMPTY + slot) * 8); }
__device__ __forceinline__ void ring_wait(uint32_t sb, const RingPos& r) { mbar_wait(sb + SM_BAR + (B_FULL + r.slot) * 8, r.par); }
constexpr uint32_t DHI_B = (1024u >> 4) | (1u << 30);
constexpr uint32_t DHI_64 = (512u >> 4) | (2u << 30);
__device__ __forceinline__ uint64_t mkd(uint32_t addr, uint32_t lbo, uint32_t hi) {
    return ((uint64_t)hi << 32) | (uint64_t)(((addr & 0x3FFFF) >> 4) | ((lbo >> 4) << 16));
}
constexpr uint32_t ONES2 = 0x3F803F80u;

__device__ __forceinline__ void finish_stats(float s0, float q0, float s1, float q1, uint32_t& nm0, uint32_t& nm1, float& r0, float& r1) {
    const float m0 = s0 * (1.f / 384.f), m1 = s1 * (1.f / 384.f);
    r0 = rsqrtf(fmaxf(q0 * (1.f / 384.f) - m0 * m0, 0.f) + 1e-5f);
    r1 = rsqrtf(fmaxf(q1 * (1.f / 384.f) - m1 * m1, 0.f) + 1e-5f);
    nm0 = pack_bf16(-m0, -m0); nm1 = pack_bf16(-m1, -m1);
}
template <int PSTRIDE, int R8>
__device__ __forceinline__ void combine_stats(uint32_t a, uint32_t& nm0, uint32_t& nm1, float& r0, float& r1) {
    float2 u[6], v[6];
#pragma unroll
    for (int i = 0; i < 6; i++) { u[i] = sm_at<float2>(a + i * PSTRIDE); v[i] = sm_at<float2>(a + i * PSTRIDE + R8); }
    const float s0 = ((u[0].x + u[1].x) + (u[2].x + u[3].x)) + (u[4].x + u[5].x), q0 = ((u[0].y + u[1].y) + (u[2].y + u[3].y)) + (u[4].y + u[5].y);
    const float s1 = ((v[0].x + v[1].x) + (v[2].x + v[3].x)) + (v[4].x + v[5].x), q1 = ((v[0].y + v[1].y) + (v[2].y + v[3].y)) + (v[4].y + v[5].y);
    finish_stats(s0, q0, s1, q1, nm0, nm1, r0, r1);
}

template <int N> __device__ __forceinline__ void wgmma_rs(float (&acc)[N / 2], const uint32_t* f, uint64_t db, int sd) {
    if constexpr (N == 128) wgmma_rs_n128(acc, f[0], f[1], f[2], f[3], db, sd);
    else if constexpr (N == 96) wgmma_rs_n96(acc, f[0], f[1], f[2], f[3], db, sd);
    else wgmma_rs_n64(acc, f[0], f[1], f[2], f[3], db, sd);
}
template <int N, int CPS, bool MEAN, bool FIXED = false, bool XTRA = false, bool PRE = false>
__device__ __forceinline__ void gemm_rs(float (&acc)[N / 2], uint32_t sb, uint32_t a, uint32_t nm0, uint32_t nm1,
                                        uint32_t s0, uint32_t stride, int lane, int arrive_bar, bool xw = false, int sync_bar = -1) {
    uint32_t f[6][16];
    if (MEAN) {
        float s[4][4];
#pragma unroll
        for (int ks = 0; ks < 4; ks++) { s[ks][0] = s[ks][1] = s[ks][2] = s[ks][3] = 0.f; }
#pragma unroll
        for (int j = 0; j < 6; j++)
#pragma unroll
            for (int ks = 0; ks < 4; ks++) {
                ldsm4((a ^ (ks << 5)) + j * 8192, f[j][4 * ks], f[j][4 * ks + 1], f[j][4 * ks + 2], f[j][4 * ks + 3]);
                mma16816(s[ks], f[j][4 * ks], f[j][4 * ks + 1], f[j][4 * ks + 2], f[j][4 * ks + 3], ONES2, ONES2);
            }
        const float m0 = ((s[0][0] + s[1][0]) + (s[2][0] + s[3][0])) * (-1.f / 384.f), m1 = ((s[0][2] + s[1][2]) + (s[2][2] + s[3][2])) * (-1.f / 384.f);
        nm0 = pack_bf16(m0, m0); nm1 = pack_bf16(m1, m1);
        STAMP(0, 2);
    }
    RingPos rp = ring_pos(FIXED ? 0 : s0), rr = rp;
    auto prep = [&](int j) {
        if (!MEAN) {
#pragma unroll
            for (int ks = 0; ks < 4; ks++) ldsm4((a ^ (ks << 5)) + j * 8192, f[j][4 * ks], f[j][4 * ks + 1], f[j][4 * ks + 2], f[j][4 * ks + 3]);
        }
#pragma unroll
        for (int i = 0; i < 16; i++) f[j][i] = hadd2_bf(f[j][i], (i & 1) ? nm1 : nm0);
    };
    if (PRE) {
#pragma unroll
        for (int j = 0; j < 6; j++) prep(j);
        if (sync_bar >= 0) bar_sync(sync_bar, 256);
    }
#pragma unroll
    for (int gq = 0; gq < 3; gq++) {
        uint64_t db[2];
        if (!PRE) { prep(2 * gq); prep(2 * gq + 1); }
#pragma unroll
        for (int u = 0; u < 2; u++) {
            const int j = 2 * gq + u;
            const bool inx = XTRA && xw && j < 3;
            if (FIXED) { if (j == 0) mbar_wait(bar_addr(sb, stride), 0); }
            else if (inx) { if (j == 0) mbar_wait(bar_addr(sb, B_W1X), 0); }
            else if (j % CPS == 0) ring_wait(sb, rp);
            db[u] = FIXED ? mkd(sb + s0 + j * 8192, 8192, DHI_B)
                          : mkd(inx ? sb + SM_A1 + j * SLOT : sb + SM_RING + rp.slot * SLOT + (j % CPS) * 8192, 8192, DHI_B);
            if (!FIXED && !inx && j % CPS == CPS - 1) ring_adv(rp, stride);
        }
        wg_fence();
#pragma unroll
        for (int u = 0; u < 2; u++)
#pragma unroll
            for (int ks = 0; ks < 4; ks++) wgmma_rs<N>(acc, &f[2 * gq + u][4 * ks], db[u] + ks * 128, (gq | u | ks) != 0);
        wg_commit();
        if (gq == 2) { if (arrive_bar >= 0) bar_arrive(arrive_bar, 256); }
        if (!FIXED && gq >= 1) {
            wg_wait<1>();
            if (!(XTRA && xw)) {
#pragma unroll
                for (int i = 0; i < 2 / CPS; i++) { ring_release(sb, rr.slot, lane); ring_adv(rr, stride); }
            } else if (gq == 2) { ring_release(sb, rr.slot, lane); ring_adv(rr, stride); }
        }
    }
    wg_wait<0>();
#pragma unroll
    for (int j = 0; j < 6; j++) pin_r(f[j]);
    pin_f(acc);
    if (!FIXED) {
#pragma unroll
        for (int i = 0; i < 2 / CPS; i++) { ring_release(sb, rr.slot, lane); ring_adv(rr, stride); }
    }
}

__device__ __forceinline__ float gelu_f(float a, float A, float B, float H) {
    const float u = a * fmaf(a * a, B, A);
    const float h = a * H;
    return fmaf(tanh_ap(u), h, h);
}

__device__ __forceinline__ unsigned ld_relaxed(const unsigned* p) { unsigned v; asm volatile("ld.relaxed.gpu.global.u32 %0, [%1];" : "=r"(v) : "l"(p) : "memory"); return v; }
__device__ __forceinline__ void poll_cnt(const unsigned* p, unsigned target, int lane) {
    if (lane == 0) {
        int it = 0;
        while ((int)(ld_relaxed(p) - target) < 0) { if (++it > (1 << 22)) __trap(); }
    }
    __syncwarp();
}
__device__ __forceinline__ void signal_cnt(unsigned* p) {
    asm volatile("red.relaxed.gpu.global.add.u32 [%0], 1;" :: "l"(p) : "memory");
}

template <int PH>
__device__ __forceinline__ void proj_block(uint32_t sb, uint32_t stage0, int c, int k, int lane, int ww, uint32_t a128) {
    const int g = lane >> 2, q4 = lane & 3, row0 = 16 * ww + g;
    constexpr int wg = 1; (void)wg;
    float acc[32];
    const uint32_t own = sb + (PH ? SM_A0 : SM_A1) + c * 8192;
    const uint32_t res = PH ? sb + SM_RES : own;
    uint32_t y[16];
#pragma unroll
    for (int jj = 0; jj < 4; jj++) ldsm4(res + (a128 ^ (jj << 5)), y[4 * jj], y[4 * jj + 1], y[4 * jj + 2], y[4 * jj + 3]);
    mbar_wait(bar_addr(sb, PH ? B_OS : B_OT), 0);
    STAMP(wg, PH ? 19 : 6);
    {
        const uint64_t da = PH ? mkd(sb + SM_A1, 16, DHI_64) : mkd(sb + SM_A0, 16, DHI_B);
        RingPos rp = ring_pos(stage0);
        uint32_t prev = 0;
#pragma unroll
        for (int st = 0; st < 3; st++) {
            ring_wait(sb, rp);
            const uint64_t db = mkd(sb + SM_RING + rp.slot * SLOT, 8192, DHI_B);
            wg_fence();
#pragma unroll
            for (int ks = 0; ks < 8; ks++)
                wgmma_ss_n64(acc, da + st * 1024 + (PH ? (ks >> 1) * 256 + (ks & 1) * 2 : (ks >> 2) * 512 + (ks & 3) * 2), db + ks * 128, (st | ks) != 0);
            wg_commit();
            if (st) { wg_wait<1>(); ring_release(sb, prev, lane); }
            prev = rp.slot; ring_adv(rp, 1);
        }
        wg_wait<0>();
        pin_f(acc);
        ring_release(sb, prev, lane);
    }
    if (lane == 0) mbar_arrive(bar_addr(sb, PH ? B_A1FREE : B_A0FREE));
    STAMP(wg, PH ? 20 : 7);
#pragma unroll
    for (int jj = 0; jj < 4; jj++) {
#pragma unroll
        for (int i = 0; i < 4; i++) y[4 * jj + i] = hadd2_bf(y[4 * jj + i], pack_bf16(acc[8 * jj + 2 * i], acc[8 * jj + 2 * i + 1]));
        stsm4(own + (a128 ^ (jj << 5)), y[4 * jj], y[4 * jj + 1], y[4 * jj + 2], y[4 * jj + 3]);
    }
    fence_async_smem();
    __syncwarp();
    uint8_t* gi = (PH ? g_x2i : g_x1i) + blockIdx.x * 8192 + ww * 2048;
    const bool leader = elect_one();
    if (leader) {
        bulk_s2g(gi, own + ww * 2048, 2048); bulk_commit();
        mbar_arrive(bar_addr(sb, PH ? B_X2 : B_X1));
    }
    if (PH) {
#pragma unroll
        for (int jj = 0; jj < 4; jj++) stsm4(res + (a128 ^ (jj << 5)), y[4 * jj], y[4 * jj + 1], y[4 * jj + 2], y[4 * jj + 3]);
    }
    float sm[4] = {0.f, 0.f, 0.f, 0.f}, ga[4] = {0.f, 0.f, 0.f, 0.f}, gb[4] = {0.f, 0.f, 0.f, 0.f};
#pragma unroll
    for (int jj = 0; jj < 4; jj++) {
        mma16816(sm, y[4 * jj], y[4 * jj + 1], y[4 * jj + 2], y[4 * jj + 3], ONES2, ONES2);
        mma16816(ga, y[4 * jj], y[4 * jj + 1], y[4 * jj + 2], y[4 * jj + 3], y[4 * jj], y[4 * jj + 2]);
        mma16816(gb, y[4 * jj], y[4 * jj + 1], y[4 * jj + 2], y[4 * jj + 3], y[4 * jj + 1], y[4 * jj + 3]);
    }
    const int src = (lane & ~3) | (g >> 1);
    const float q0 = __shfl_sync(0xffffffffu, (g & 1) ? ga[1] : ga[0], src), q1 = __shfl_sync(0xffffffffu, (g & 1) ? gb[3] : gb[2], src);
    const uint32_t sta = sb + SM_ST + c * 512 + row0 * 8, stb = bar_addr(sb, PH ? B_ST3 : B_ST2);
#pragma unroll 1
    for (int d = q4; d < CS; d += 4) {
        const uint32_t ra = mapa(sta, d), rb = mapa(stb, d);
        st_async_v2(ra, __float_as_uint(sm[0]), __float_as_uint(q0), rb);
        st_async_v2(ra + 64, __float_as_uint(sm[2]), __float_as_uint(q1), rb);
    }
    if (leader) { bulk_wait<0>(); bulk_g2s_mc(own + ww * 2048, gi, 2048, bar_addr(sb, PH ? B_X2 : B_X1), (uint16_t)(0x3F & ~(1 << c))); }
    if (PH == 0) {
        if (q4 < 2) {
            const int tok = (2 * q4 + (g & 1)) * 256 + 16 * k + 4 * ww + (g >> 1);
            g_part[tok * 6 + c] = q4 ? make_float2(sm[2], q1) : make_float2(sm[0], q0);
        }
        __syncwarp();
        if (lane == 0) mbar_arrive(bar_addr(sb, B_X1ST));
    }
    __syncwarp();
    STAMP(wg, PH ? 31 : 8);
}

#define G1PRE true
constexpr float SL2 = 0.10206207261596577f * 1.4426950408889634f;

template <int PHASES>
__global__ void __launch_bounds__(NTHREADS, 1) fused_kernel(const __grid_constant__ Params p) {
    const uint32_t sb = smem_u32(smem);
    const int tid = threadIdx.x, lane = tid & 31;
    const int warp = __shfl_sync(0xffffffffu, tid >> 5, 0);
    uint32_t c_u; asm("mov.u32 %0, %%cluster_ctarank;" : "=r"(c_u));
    const int c = (int)c_u;
    const int k = blockIdx.x / CS;
    const bool att = c < 4;
    constexpr bool P1 = (PHASES & 1) != 0, P2 = (PHASES & 2) != 0;
    constexpr int UBEG = P1 ? 0 : 15;

    if (warp == 8) {
        if (elect_one()) {
            mbar_init(bar_addr(sb, B_X), 1);
            mbar_init(bar_addr(sb, B_VW), 1);
#pragma unroll
            for (int i = 0; i < 6; i++) mbar_init(bar_addr(sb, B_FULL + i), 1);
            asm volatile("fence.mbarrier_init.release.cluster;" ::: "memory");
            fence_async_smem();
        }
        __syncwarp();
        bar_arrive(9, NTHREADS);
        if (P1 && elect_one()) {
            const uint32_t b = bar_addr(sb, B_X);
            mbar_expect_tx(b, 49152);
#pragma unroll 1
            for (int j = 0; j < 6; j++) tma_ld5(sb + SM_A1 + j * 8192, &p.tm_x, 64 * j, 0, 0, 0, 4 * k, b);
        }
        __syncwarp();
        bar_sync(10, 64);
    } else if (warp == 11) {
        if (elect_one()) {
#pragma unroll
            for (int i = B_EMPTY; i < B_COUNT; i++) if (i != B_X && i != B_VW) mbar_init(bar_addr(sb, i), bar_count(i));
#pragma unroll
            for (int i = B_EMPTY; i < B_COUNT; i++) if (bar_tx(i)) mbar_expect_tx(bar_addr(sb, i), bar_tx(i));
            asm volatile("fence.mbarrier_init.release.cluster;" ::: "memory");
        }
        __syncwarp();
        bar_arrive(9, NTHREADS);
        bar_arrive(10, 64);
    } else {
        bar_sync(9, NTHREADS);
        if (warp == 10 && elect_one()) {
#pragma unroll 1
            for (int s = 0; s < 6; s++) {
                const uint32_t e = p.stage[c][UBEG + s];
                const int x0 = e & 2047, y0 = (e >> 11) & 2047, mode = (e >> 25) & 3;
                const CUtensorMap* tm = &p.tm_w[(e >> 22) & 7];
                const uint32_t fb = bar_addr(sb, B_FULL + s), dst = sb + SM_RING + s * SLOT;
                mbar_expect_tx(fb, SLOT);
                tma_ld2(dst, tm, x0, y0, fb);
                tma_ld2(dst + 8192, tm, x0 + (mode == 0 ? 384 : (mode == 2 ? 64 : 0)), y0 + (mode == 1 ? 64 : 0), fb);
            }
        }
        __syncwarp();
    }
    asm volatile("barrier.cluster.arrive.relaxed.aligned;" ::: "memory");

    if (warp >= 8) {
        asm volatile("setmaxnreg.dec.sync.aligned.u32 40;");
        if (warp == 8 || warp == 10) {
            const int odd = warp == 10;
            const int nst = (P2 ? (att ? 45 : 39) : 15) - UBEG;
            const uint32_t* tbl = &p.stage[c][UBEG];
            uint32_t slot = odd, par = 0;
            uint32_t e = tbl[6 + odd];
#pragma unroll 1
            for (int s = 6 + odd; s < nst; s += 2) {
                const int x0 = e & 2047, y0 = (e >> 11) & 2047, mode = (e >> 25) & 3, gate = e >> 27;
                const CUtensorMap* tm = &p.tm_w[(e >> 22) & 7];
                const int x1 = x0 + (mode == 0 ? 384 : (mode == 2 ? 64 : 0)), y1 = y0 + (mode == 1 ? 64 : 0);
                e = tbl[s + 2];
                const uint32_t fb = bar_addr(sb, B_FULL + slot), dst = sb + SM_RING + slot * SLOT;
                if (gate) mbar_wait_trap(bar_addr(sb, gate == 1 ? B_VFREE : B_KVISS), 0);
                mbar_wait_trap(bar_addr(sb, B_EMPTY + slot), par);
                if (elect_one()) {
                    mbar_expect_tx(fb, SLOT);
                    tma_ld2(dst, tm, x0, y0, fb);
                    tma_ld2(dst + 8192, tm, x1, y1, fb);
                }
                __syncwarp();
                slot += 2; if (slot >= 6) { slot -= 6; par ^= 1; }
            }
            STAMP1(2, odd);
            if (odd) mbar_wait_trap(bar_addr(sb, B_DONE), 0);
        } else if (warp == 9) {
            unsigned epoch = 0;
            if (PHASES == 3) { epoch = *(volatile unsigned*)&g_epoch + 1; if (epoch == 0) __trap(); }
            if (P1 && elect_one()) {
                const uint32_t b = bar_addr(sb, B_VW);
                mbar_expect_tx(b, 49152);
#pragma unroll 1
                for (int j = 0; j < 6; j++) tma_ld2(sb + SM_A0 + j * 8192, &p.tm_w[0], 768 + 64 * c, 64 * j, b);
            }
            __syncwarp();
            if (P1) mbar_wait_trap(bar_addr(sb, B_X), 0);
            if (lane >= 1 && lane < 6) {
                const int per = (lane == 2 ? 9216 : (lane >= 4 ? 12288 : 3072));
                bulk_prefetch((const char*)p.wptr[lane] + (size_t)blockIdx.x * per, per);
            }
            if (P2) {
                const int row0 = k * 64;
                if (P1) mbar_wait_trap(bar_addr(sb, B_A0FREE), 0);
                if (PHASES == 3) poll_cnt(g_cnt + 32 * (k & 3), epoch * 24, lane);
                STAMP1(2, 2);
                if (elect_one()) {
                    const uint32_t b = bar_addr(sb, B_X1P);
                    mbar_expect_tx(b, att ? 49152 + 8192 + 3072 : 8192);
                    tma_ld2(sb + SM_RES, &p.tm_x1l, 64 * c, row0, b);
                    if (att) {
                        bulk_g2s(sb + SM_SC, g_part + row0 * 6, 3072, b);
#pragma unroll 1
                        for (int j = 0; j < 6; j++) tma_ld2(sb + SM_A0 + j * 8192, &p.tm_x1l, 64 * j, row0, b);
                    }
                }
                __syncwarp();
                if (att) {
                    if (PHASES == 3) {
                        poll_cnt(g_cnt + 128, epoch * 96, lane);
                        if (blockIdx.x == 0 && lane == 0) *(volatile unsigned*)&g_epoch = epoch;
                    }
                    STAMP1(2, 3);
#pragma unroll 1
                    for (int i = 0; i < 4; i++) {
                        if (i == 2) mbar_wait_trap(bar_addr(sb, B_QDONE), 0);
                        if (elect_one()) {
                            const uint32_t b = bar_addr(sb, B_K0 + i);
                            mbar_expect_tx(b, 24576);
                            tma_ld3(sb + (i < 2 ? SM_A1 : SM_A0) + (i & 1) * 24576, &p.tm_kvl, 0, (k >> 2) * 256 + 128 * (i & 1), (i < 2 ? 0 : 12) + 3 * c, b);
                        }
                        __syncwarp();
                    }
                    if (lane == 0) mbar_arrive(bar_addr(sb, B_KVISS));
                    STAMP1(2, 4);
                }
                mbar_wait_trap(bar_addr(sb, B_A1FREE), 0);
                mbar_wait_trap(bar_addr(sb, B_X2), 0);
                if (elect_one()) {
                    const uint32_t b = bar_addr(sb, B_W1X);
                    mbar_expect_tx(b, 49152);
#pragma unroll 1
                    for (int j = 0; j < 6; j++) tma_ld2(sb + SM_A1 + j * 8192, &p.tm_w[4], 256 * c + 128 + 64 * (j & 1), 64 * (j >> 1), b);
                }
                __syncwarp();
            }
        } else if (warp == 11) {
            if (P1 && elect_one()) {
                mbar_wait_trap(bar_addr(sb, B_X1ST), 0);
                tma_st5(&p.tm_x1s, 64 * c, 0, 0, 0, 4 * k, sb + SM_A1 + c * 8192);
                bulk_commit(); bulk_wait<0>();
                if (PHASES == 3) signal_cnt(g_cnt + 32 * (k >> 2));
                STAMP1(2, 6);
                mbar_wait_trap(bar_addr(sb, B_KVST), 0);
                STAMP1(2, 7);
                tma_st5(&p.tm_kvs, 128 * c, 0, 0, 0, 4 * k, sb + SM_STG);
                tma_st5(&p.tm_kvs, 128 * c + 64, 0, 0, 0, 4 * k, sb + SM_STG + 8192);
                bulk_commit(); bulk_wait<0>();
                if (PHASES == 3) signal_cnt(g_cnt + 128);
                mbar_arrive(bar_addr(sb, B_STGFREE));
                STAMP1(2, 9);
            }
        }
    } else {
        asm volatile("setmaxnreg.inc.sync.aligned.u32 232;");
        const int wg = warp >> 2, ww = warp & 3;
        const int g = lane >> 2, q4 = lane & 3;
        const int row0 = 16 * ww + g;
        const int lrow = 16 * ww + (lane & 15);
        const uint32_t hi = lane >> 4;
        const uint32_t a128 = lrow * 128 + (((lrow & 7) ^ hi) << 4);
        const uint32_t a64 = lrow * 64 + ((((lrow >> 1) & 3) ^ hi) << 4);
        const bool diag = (q4 == (g >> 1));
        STAMP(wg, 0);
        constexpr uint32_t SQ = P1 ? 15 : 0;
        const uint32_t sp = SQ + (att ? 6 : 0);
        uint32_t nm0 = 0, nm1 = 0; float r0, r1;
        if (P1) {
            mbar_wait(bar_addr(sb, B_X), 0);
            STAMP(wg, 1);
            const uint32_t tile = sb + SM_A1;
            if (wg == 0) {
                float acc[64];
                uint32_t sdst[2][3], sbar[2][3];
#pragma unroll
                for (int a = 0; a < 2; a++) {
                    const int un = 2 * c + a, h = (un * 43) >> 7, slot = un - 3 * h;
#pragma unroll
                    for (int d = 0; d < 3; d++) {
                        const int u2 = 3 * h + d;
                        sdst[a][d] = mapa(sb + SM_SC + (u2 & 1) * 3072 + slot * 1024 + row0 * 16, u2 >> 1);
                        sbar[a][d] = mapa(bar_addr(sb, B_SC), u2 >> 1);
                    }
                }
                gemm_rs<128, 1, true>(acc, sb, tile + a128, 0, 0, 0, 1, lane, 2);
                STAMP(wg, 3);
                asm volatile("barrier.cluster.wait.aligned;" ::: "memory");
#pragma unroll
                for (int a = 0; a < 2; a++) {
                    float s0[4] = {0.f, 0.f, 0.f, 0.f}, s1[4] = {0.f, 0.f, 0.f, 0.f};
#pragma unroll
                    for (int s = 0; s < 2; s++) {
                        const int o = 16 * a + 8 * s;
                        const uint32_t q0 = pack_bf16(acc[o], acc[o + 1]), q1 = pack_bf16(acc[o + 2], acc[o + 3]);
                        const uint32_t q2 = pack_bf16(acc[o + 4], acc[o + 5]), q3 = pack_bf16(acc[o + 6], acc[o + 7]);
                        mma16816(s0, q0, q1, q2, q3, pack_bf16(acc[32 + o], acc[33 + o]), pack_bf16(acc[36 + o], acc[37 + o]));
                        mma16816(s1, q0, q1, q2, q3, pack_bf16(acc[34 + o], acc[35 + o]), pack_bf16(acc[38 + o], acc[39 + o]));
                    }
                    if (diag) {
#pragma unroll
                        for (int d = 0; d < 3; d++) {
                            st_async_v4(sdst[a][d], __float_as_uint(s0[0]), __float_as_uint(s0[1]), __float_as_uint(s1[0]), __float_as_uint(s1[1]), sbar[a][d]);
                            st_async_v4(sdst[a][d] + 128, __float_as_uint(s0[2]), __float_as_uint(s0[3]), __float_as_uint(s1[2]), __float_as_uint(s1[3]), sbar[a][d]);
                        }
                    }
                }
                STAMP(wg, 4);
            } else {
                {
                    float s0 = 0.f, q0 = 0.f, s1 = 0.f, q1 = 0.f;
                    uint32_t a = tile + a128;
#pragma unroll 1
                    for (int j = 0; j < 12; j++) {
                        uint32_t t[8];
                        ldsm4(a, t[0], t[1], t[2], t[3]);
                        ldsm4(a ^ 32, t[4], t[5], t[6], t[7]);
                        a = (j & 1) ? (a ^ 64) + 8192 : (a ^ 64);
#pragma unroll
                        for (int i = 0; i < 8; i++) {
                            const float lo = bf_lo(t[i]), hi2 = bf_hi(t[i]);
                            if (i & 1) { s1 += lo + hi2; q1 = fmaf(lo, lo, fmaf(hi2, hi2, q1)); } else { s0 += lo + hi2; q0 = fmaf(lo, lo, fmaf(hi2, hi2, q0)); }
                        }
                    }
                    s0 += __shfl_xor_sync(0xffffffffu, s0, 1); q0 += __shfl_xor_sync(0xffffffffu, q0, 1);
                    s1 += __shfl_xor_sync(0xffffffffu, s1, 1); q1 += __shfl_xor_sync(0xffffffffu, q1, 1);
                    s0 += __shfl_xor_sync(0xffffffffu, s0, 2); q0 += __shfl_xor_sync(0xffffffffu, q0, 2);
                    s1 += __shfl_xor_sync(0xffffffffu, s1, 2); q1 += __shfl_xor_sync(0xffffffffu, q1, 2);
                    finish_stats(s0, q0, s1, q1, nm0, nm1, r0, r1);
                }
                STAMP(wg, 2);
                asm volatile("barrier.cluster.wait.aligned;" ::: "memory");
                float acc[32];
                gemm_rs<64, 2, false, true, false, true>(acc, sb, tile + a128, nm0, nm1, SM_A0, B_VW, lane, -1, false, 2);
                if (lane < CS) mbar_arrive_remote(mapa(bar_addr(sb, B_VFREE), lane));
                STAMP(wg, 3);
                uint32_t vb[16];
#pragma unroll
                for (int j = 0; j < 8; j++) {
                    vb[2 * j] = movm(pack_bf16(acc[4 * j], acc[4 * j + 1]));
                    vb[2 * j + 1] = movm(pack_bf16(acc[4 * j + 2], acc[4 * j + 3]));
                }
                const float p0 = __shfl_xor_sync(0xffffffffu, r0, 4), p1 = __shfl_xor_sync(0xffffffffu, r1, 4);
                const bool odd = g & 1;
                const float rk0 = odd ? p0 : r0, rk1 = odd ? r0 : p0, rk2 = odd ? p1 : r1, rk3 = odd ? r1 : p1;
                mbar_wait_cl(bar_addr(sb, B_SC), 0);
                STAMP(wg, 4);
                uint32_t o[16], pa[2][4];
#pragma unroll
                for (int a = 0; a < 2; a++)
#pragma unroll
                    for (int i = 0; i < 2; i++) {
                        const uint32_t ad = SM_SC + a * 3072 + (row0 + 8 * i) * 16;
                        const float4 x0 = sm_at<float4>(ad), x1 = sm_at<float4>(ad + 1024), x2 = sm_at<float4>(ad + 2048);
                        const float f = (i ? r1 : r0) * SL2;
                        const float s0 = (x0.x + x1.x + x2.x) * (f * rk0), s1 = (x0.y + x1.y + x2.y) * (f * rk1);
                        const float s2 = (x0.z + x1.z + x2.z) * (f * rk2), s3 = (x0.w + x1.w + x2.w) * (f * rk3);
                        const float m = fmaxf(fmaxf(s0, s1), fmaxf(s2, s3));
                        const float e0 = ex2(s0 - m), e1 = ex2(s1 - m), e2 = ex2(s2 - m), e3 = ex2(s3 - m);
                        float inv; asm("rcp.approx.ftz.f32 %0, %1;" : "=f"(inv) : "f"((e0 + e1) + (e2 + e3)));
                        inv = diag ? inv : 0.f;
                        pa[a][i] = pack_bf16(e0 * (inv * rk0), e1 * (inv * rk1));
                        pa[a][2 + i] = pack_bf16(e2 * (inv * rk2), e3 * (inv * rk3));
                    }
#pragma unroll
                for (int j = 0; j < 8; j++) {
                    float d[4] = {0.f, 0.f, 0.f, 0.f};
                    mma16816(d, pa[j >> 2][0], pa[j >> 2][1], pa[j >> 2][2], pa[j >> 2][3], vb[2 * j], vb[2 * j + 1]);
                    o[2 * j] = pack_bf16(d[0], d[1]); o[2 * j + 1] = pack_bf16(d[2], d[3]);
                }
#pragma unroll
                for (int jj = 0; jj < 4; jj++)
                    stsm4(sb + SM_STG + (a128 ^ (jj << 5)), o[4 * jj], o[4 * jj + 1], o[4 * jj + 2], o[4 * jj + 3]);
                fence_async_smem();
                __syncwarp();
                if (elect_one()) {
                    uint8_t* gi = g_ot + blockIdx.x * 8192 + ww * 2048;
                    bulk_s2g(gi, sb + SM_STG + ww * 2048, 2048); bulk_commit();
                    mbar_wait(bar_addr(sb, B_VFREE), 0);
                    bulk_wait<0>();
                    bulk_g2s_mc(sb + SM_A0 + c * 8192 + ww * 2048, gi, 2048, bar_addr(sb, B_OT), 0x3F);
                }
                __syncwarp();
                STAMP(wg, 5);
                proj_block<0>(sb, 6, c, k, lane, ww, a128);
            }
            if (wg == 0) {
                mbar_wait_cl(bar_addr(sb, B_ST2), 0);
                combine_stats<512, 64>(SM_ST + row0 * 8, nm0, nm1, r0, r1);
                mbar_wait(bar_addr(sb, B_X1), 0);
                STAMP(wg, 9);
                float acc[64];
                gemm_rs<128, 1, false>(acc, sb, sb + SM_A1 + a128, nm0, nm1, 9, 1, lane, -1);
                STAMP(wg, 10);
#pragma unroll
                for (int jj = 0; jj < 8; jj++)
                    stsm4(sb + SM_STG + (jj >> 2) * 8192 + (a128 ^ ((jj & 3) << 5)),
                          pack_bf16(acc[8 * jj] * r0, acc[8 * jj + 1] * r0), pack_bf16(acc[8 * jj + 2] * r1, acc[8 * jj + 3] * r1),
                          pack_bf16(acc[8 * jj + 4] * r0, acc[8 * jj + 5] * r0), pack_bf16(acc[8 * jj + 6] * r1, acc[8 * jj + 7] * r1));
                fence_async_smem();
                __syncwarp();
                if (lane == 0) mbar_arrive(bar_addr(sb, B_KVST));
                STAMP(wg, 11);
            }
        } else {
            asm volatile("barrier.cluster.wait.aligned;" ::: "memory");
        }
        if (P2) {
            if (!att && lane < 4) { if (wg == 0) { mbar_arrive_remote(mapa(bar_addr(sb, B_KFREE), lane)); mbar_arrive_remote(mapa(bar_addr(sb, B_KFREE), lane)); } }
            mbar_wait(bar_addr(sb, B_X1P), 0);
            STAMP(wg, 12);
            if (att) {
                if (wg == 0) {
                    float acc[48];
                    combine_stats<8, 384>(SM_SC + row0 * 48, nm0, nm1, r0, r1);
                    gemm_rs<96, 1, false>(acc, sb, sb + SM_A0 + a128, nm0, nm1, SQ, 1, lane, -1);
                    if (lane == 0) mbar_arrive(bar_addr(sb, B_QDONE));
                    if (P1) mbar_wait(bar_addr(sb, B_STGFREE), 0);
#pragma unroll
                    for (int jj = 0; jj < 6; jj++)
                        stsm4(sb + SM_STG + (jj >> 1) * 4096 + (a64 ^ ((jj & 1) << 5)),
                              pack_bf16(acc[8 * jj] * r0, acc[8 * jj + 1] * r0), pack_bf16(acc[8 * jj + 2] * r1, acc[8 * jj + 3] * r1),
                              pack_bf16(acc[8 * jj + 4] * r0, acc[8 * jj + 5] * r0), pack_bf16(acc[8 * jj + 6] * r1, acc[8 * jj + 7] * r1));
                    fence_async_smem();
                }
                bar_sync(1, 256);
                STAMP(wg, 13);
                float s[64];
                mbar_wait(bar_addr(sb, B_K0 + wg), 0);
                STAMP(wg, 14);
                {
                    const uint64_t da = mkd(sb + SM_STG, 16, DHI_64), db = mkd(sb + SM_A1 + wg * 24576, 16, DHI_64);
                    wg_fence();
#pragma unroll
                    for (int ks = 0; ks < 6; ks++)
                        wgmma_ss_n128_bn(s, da + (ks >> 1) * 256 + (ks & 1) * 2, db + (ks >> 1) * 512 + (ks & 1) * 2, ks != 0);
                    wg_commit();
                    wg_wait<0>();
                    pin_f(s);
                }
                if (lane < 4) mbar_arrive_remote(mapa(bar_addr(sb, B_KFREE), lane));
                STAMP(wg, 15);
                float m0 = fmaxf(s[0], s[1]), m1 = fmaxf(s[2], s[3]);
#pragma unroll
                for (int j = 1; j < 16; j++) { m0 = fmaxf(m0, fmaxf(s[4 * j], s[4 * j + 1])); m1 = fmaxf(m1, fmaxf(s[4 * j + 2], s[4 * j + 3])); }
                m0 = fmaxf(m0, __shfl_xor_sync(0xffffffffu, m0, 1)); m1 = fmaxf(m1, __shfl_xor_sync(0xffffffffu, m1, 1));
                m0 = fmaxf(m0, __shfl_xor_sync(0xffffffffu, m0, 2)); m1 = fmaxf(m1, __shfl_xor_sync(0xffffffffu, m1, 2));
                m0 *= SL2; m1 *= SL2;
                float l0 = 0.f, l1 = 0.f;
                uint32_t pa[32];
#pragma unroll
                for (int j = 0; j < 16; j++) {
                    const float e0 = ex2v(fmaf(s[4 * j], SL2, -m0)), e1 = ex2v(fmaf(s[4 * j + 1], SL2, -m0));
                    const float e2 = ex2v(fmaf(s[4 * j + 2], SL2, -m1)), e3 = ex2v(fmaf(s[4 * j + 3], SL2, -m1));
                    l0 += e0 + e1; l1 += e2 + e3;
                    pa[2 * j] = pack_bf16(e0, e1); pa[2 * j + 1] = pack_bf16(e2, e3);
                }
                STAMP(wg, 16);
                float o[48];
                mbar_wait(bar_addr(sb, B_V0 + wg), 0);
                {
                    const uint64_t db = mkd(sb + SM_A0 + wg * 24576, 8192, DHI_64);
                    wg_fence();
#pragma unroll
                    for (int ks = 0; ks < 8; ks++)
                        wgmma_rs_n96(o, pa[4 * ks], pa[4 * ks + 1], pa[4 * ks + 2], pa[4 * ks + 3], db + ks * 64, ks != 0);
                    wg_commit();
                }
                l0 += __shfl_xor_sync(0xffffffffu, l0, 1); l1 += __shfl_xor_sync(0xffffffffu, l1, 1);
                l0 += __shfl_xor_sync(0xffffffffu, l0, 2); l1 += __shfl_xor_sync(0xffffffffu, l1, 2);
                if (q4 == 0) { sm_at<float2>(SM_ML + wg * 512 + row0 * 8) = make_float2(m0, l0); sm_at<float2>(SM_ML + wg * 512 + row0 * 8 + 64) = make_float2(m1, l1); }
                wg_wait<0>();
                pin_r(pa); pin_f(o);
                STAMP(wg, 17);
                const uint32_t t16 = (tid & 127) * 16;
                const uint32_t scr_own = SM_A0 + wg * 24576 + t16, scr_oth = SM_A0 + (wg ^ 1) * 24576 + t16;
                if (wg == 0) {
#pragma unroll
                    for (int v = 0; v < 6; v++) sm_at<float4>(scr_own + v * 2048) = make_float4(o[24 + 4 * v], o[25 + 4 * v], o[26 + 4 * v], o[27 + 4 * v]);
                } else {
#pragma unroll
                    for (int v = 0; v < 6; v++) sm_at<float4>(scr_own + v * 2048) = make_float4(o[4 * v], o[4 * v + 1], o[4 * v + 2], o[4 * v + 3]);
                }
                bar_sync(1, 256);
                float4 y[6];
#pragma unroll
                for (int v = 0; v < 6; v++) y[v] = sm_at<float4>(scr_oth + v * 2048);
                const float2 x0 = sm_at<float2>(SM_ML + (wg ^ 1) * 512 + row0 * 8), x1 = sm_at<float2>(SM_ML + (wg ^ 1) * 512 + row0 * 8 + 64);
                const float mm0 = fmaxf(m0, x0.x), mm1 = fmaxf(m1, x1.x);
                float a0 = ex2(m0 - mm0), b0 = ex2(x0.x - mm0), a1 = ex2(m1 - mm1), b1 = ex2(x1.x - mm1);
                float i0, i1;
                asm("rcp.approx.ftz.f32 %0, %1;" : "=f"(i0) : "f"(a0 * l0 + b0 * x0.y));
                asm("rcp.approx.ftz.f32 %0, %1;" : "=f"(i1) : "f"(a1 * l1 + b1 * x1.y));
                a0 *= i0; b0 *= i0; a1 *= i1; b1 *= i1;
#define COMBINE(O)                                                                                                                       \
                _Pragma("unroll") for (int jj = 0; jj < 3; jj++) {                                                                       \
                    const float4 ya = y[2 * jj], yb = y[2 * jj + 1];                                                                     \
                    const int u = (O) / 8 + jj;                                                                                          \
                    const float* w = &o[(O) + 8 * jj];                                                                                   \
                    stsm4(sb + SM_STG + (u >> 1) * 4096 + (a64 ^ ((u & 1) << 5)),                                                        \
                          pack_bf16(a0 * w[0] + b0 * ya.x, a0 * w[1] + b0 * ya.y), pack_bf16(a1 * w[2] + b1 * ya.z, a1 * w[3] + b1 * ya.w),  \
                          pack_bf16(a0 * w[4] + b0 * yb.x, a0 * w[5] + b0 * yb.y), pack_bf16(a1 * w[6] + b1 * yb.z, a1 * w[7] + b1 * yb.w)); \
                }
                if (wg == 0) { COMBINE(0) } else { COMBINE(24) }
#undef COMBINE
                fence_async_smem();
                bar_sync(1, 256);
                if (warp < 3 && elect_one()) {
                    uint8_t* gi = g_os + (k * 4 + c) * 12288 + warp * 4096;
                    bulk_s2g(gi, sb + SM_STG + warp * 4096, 4096); bulk_commit();
                    mbar_wait(bar_addr(sb, B_KFREE), 0);
                    bulk_wait<0>();
                    bulk_g2s_mc(sb + SM_A1 + c * 12288 + warp * 4096, gi, 4096, bar_addr(sb, B_OS), 0x3F);
                }
                __syncwarp();
                STAMP(wg, 18);
            }
            if (wg == 1) proj_block<1>(sb, sp, c, k, lane, ww, a128);
            mbar_wait_cl(bar_addr(sb, B_ST3), 0);
            combine_stats<512, 64>(SM_ST + row0 * 8, nm0, nm1, r0, r1);
            mbar_wait(bar_addr(sb, B_X2), 0);
            STAMP(wg, 21);
            uint32_t hp[32];
            {
                float h[64];
                gemm_rs<128, 1, false, false, true, G1PRE>(h, sb, sb + SM_A0 + a128, nm0, nm1, sp + 3 + 6 * wg, 1, lane, 4 + wg, wg == 1, wg == 1 ? 4 : -1);
                STAMP(wg, 22);
                if (wg == 1 && lane < 5) { int d = c + 1 + lane; if (d >= 6) d -= 6; mbar_arrive_remote(mapa(bar_addr(sb, B_LAND), d)); }
                const float k0 = 0.7978845608028654f, k1 = 0.7978845608028654f * 0.044715f;
                const float A0 = k0 * r0, B0 = k1 * r0 * r0 * r0, H0 = 0.5f * r0, A1 = k0 * r1, B1 = k1 * r1 * r1 * r1, H1 = 0.5f * r1;
                const uint32_t dst = sb + (wg ? SM_A1 : SM_STG);
#pragma unroll
                for (int jj = 0; jj < 8; jj++) {
                    hp[4 * jj] = pack_bf16(gelu_f(h[8 * jj], A0, B0, H0), gelu_f(h[8 * jj + 1], A0, B0, H0));
                    hp[4 * jj + 1] = pack_bf16(gelu_f(h[8 * jj + 2], A1, B1, H1), gelu_f(h[8 * jj + 3], A1, B1, H1));
                    hp[4 * jj + 2] = pack_bf16(gelu_f(h[8 * jj + 4], A0, B0, H0), gelu_f(h[8 * jj + 5], A0, B0, H0));
                    hp[4 * jj + 3] = pack_bf16(gelu_f(h[8 * jj + 6], A1, B1, H1), gelu_f(h[8 * jj + 7], A1, B1, H1));
                    stsm4(dst + (jj >> 2) * 8192 + (a128 ^ ((jj & 3) << 5)), hp[4 * jj], hp[4 * jj + 1], hp[4 * jj + 2], hp[4 * jj + 3]);
                }
            }
            if (wg == 0) { bar_arrive(6, 256); bar_sync(5, 256); }
            else bar_arrive(7, 256);
            STAMP(wg, 23);
            float acc2[3][32];
            const uint32_t t16 = (tid & 127) * 16;
            {
                const RingPos r1p = ring_pos(sp + 12 + 3 * wg);
                {
                    const uint64_t db = mkd(sb + SM_RING + r1p.slot * SLOT, 8192, DHI_B);
#pragma unroll
                    for (int l = 0; l < 3; l++) {
                        mbar_wait(sb + SM_BAR + (B_FULL + r1p.slot + l) * 8, r1p.par);
                        wg_fence();
#pragma unroll
                        for (int ks = 0; ks < 8; ks++) wgmma_rs_n64(acc2[l], hp[4 * ks], hp[4 * ks + 1], hp[4 * ks + 2], hp[4 * ks + 3], db + l * 1024 + ks * 128, ks != 0);
                        wg_commit();
                        if (l) { wg_wait<1>(); ring_release(sb, r1p.slot + l - 1, lane); }
                    }
                    wg_wait<0>();
                    pin_r(hp);
                    ring_release(sb, r1p.slot + 2, lane);
                }
                STAMP(wg, 24);
                bar_sync(wg == 0 ? 7 : 6, 256);
                uint32_t ho[32];
                const uint32_t src = sb + (wg ? SM_STG : SM_A1);
#pragma unroll
                for (int jj = 0; jj < 8; jj++) ldsm4(src + (jj >> 2) * 8192 + (a128 ^ ((jj & 3) << 5)), ho[4 * jj], ho[4 * jj + 1], ho[4 * jj + 2], ho[4 * jj + 3]);
                RingPos rp = ring_pos(sp + 18 + wg), rr = rp;
#define G2_ISSUE(L)                                                                                                                   \
                {                                                                                                                       \
                    ring_wait(sb, rp);                                                                                                  \
                    const uint64_t db = mkd(sb + SM_RING + rp.slot * SLOT, 8192, DHI_B);                                                \
                    wg_fence();                                                                                                         \
                    _Pragma("unroll") for (int ks = 0; ks < 8; ks++)                                                                    \
                        wgmma_rs_n64(acc2[L], ho[4 * ks], ho[4 * ks + 1], ho[4 * ks + 2], ho[4 * ks + 3], db + ks * 128, 1);            \
                    wg_commit();                                                                                                        \
                    ring_adv(rp, 2);                                                                                                    \
                }
#define G2_SEND(L)                                                                                                                    \
                {                                                                                                                       \
                    pin_f(acc2[L]);                                                                                                     \
                    ring_release(sb, rr.slot, lane);                                                                                    \
                    ring_adv(rr, 2);                                                                                                    \
                    const int kk = 2 * L + wg;                                                                                          \
                    if (kk < 5) {                                                                                                       \
                        int d = c + 1 + kk; if (d >= 6) d -= 6;                                                                         \
                        const uint32_t dst = mapa(sb + SM_A0 + c * 8192 + t16, d), rb = mapa(bar_addr(sb, B_PART), d);                  \
                        _Pragma("unroll") for (int v = 0; v < 4; v++) {                                                                 \
                            const float* z = &acc2[L][8 * v];                                                                           \
                            st_async_v4(dst + v * 2048, pack_bf16(z[0], z[1]), pack_bf16(z[2], z[3]), pack_bf16(z[4], z[5]), pack_bf16(z[6], z[7]), rb); \
                        }                                                                                                               \
                    }                                                                                                                   \
                }
                STAMP(wg, 25);
                G2_ISSUE(0) G2_ISSUE(1)
                mbar_wait(bar_addr(sb, B_LAND), 0);
                wg_wait<1>(); G2_SEND(0)
                G2_ISSUE(2)
                wg_wait<1>(); G2_SEND(1)
                wg_wait<0>(); G2_SEND(2)
                pin_r(ho);
#undef G2_ISSUE
#undef G2_SEND
            }
            STAMP(wg, 26);
            if (wg == 1) {
                mbar_wait_cl(bar_addr(sb, B_PART), 0);
                STAMP(wg, 27);
                const uint32_t idf = (2 * q4 == g ? 0x3F80u : 0u) | (2 * q4 + 1 == g ? 0x3F800000u : 0u);
#pragma unroll
                for (int i = 1; i < 6; i++) {
                    int src = c + i; if (src >= 6) src -= 6;
#pragma unroll
                    for (int v = 0; v < 4; v++) {
                        const uint4 y = sm_at<uint4>(SM_A0 + src * 8192 + v * 2048 + t16);
                        mma16816p(&acc2[2][8 * v], y.x, y.y, y.z, y.w, idf, 0u);
                        mma16816p(&acc2[2][4 + 8 * v], y.x, y.y, y.z, y.w, 0u, idf);
                    }
                }
#pragma unroll
                for (int jj = 0; jj < 4; jj++) {
                    uint32_t r[4];
                    const uint32_t ad = sb + SM_RES + (a128 ^ (jj << 5));
                    ldsm4(ad, r[0], r[1], r[2], r[3]);
#pragma unroll
                    for (int i = 0; i < 4; i++) r[i] = hadd2_bf(r[i], pack_bf16(acc2[2][8 * jj + 2 * i], acc2[2][8 * jj + 2 * i + 1]));
                    stsm4(ad, r[0], r[1], r[2], r[3]);
                }
                fence_async_smem();
                __syncwarp();
                if (elect_one()) {
                    tma_st2(&p.tm_out, 64 * c, k * 64 + 16 * ww, sb + SM_RES + ww * 2048);
                    bulk_commit(); bulk_wait_read<0>();
                }
                __syncwarp();
            }
            STAMP(wg, 28);
        }
        if (lane == 0) mbar_arrive(bar_addr(sb, B_DONE));
        asm volatile("barrier.cluster.arrive.relaxed.aligned;" ::: "memory");
        asm volatile("barrier.cluster.wait.aligned;" ::: "memory");
        STAMP(wg, 29);
    }
}

}

typedef CUresult (*EncodeFn)(CUtensorMap*, CUtensorMapDataType, cuuint32_t, void*, const cuuint64_t*, const cuuint64_t*, const cuuint32_t*,
                             const cuuint32_t*, CUtensorMapInterleave, CUtensorMapSwizzle, CUtensorMapL2promotion, CUtensorMapFloatOOBfill);

static void encode_map(EncodeFn enc, CUtensorMap* tm, const void* base, int rank, const cuuint64_t* dims, const cuuint64_t* strides,
                       const cuuint32_t* box, CUtensorMapSwizzle swz) {
    cuuint32_t es[5] = {1, 1, 1, 1, 1};
    enc(tm, CU_TENSOR_MAP_DATA_TYPE_BFLOAT16, (cuuint32_t)rank, const_cast<void*>(base), dims, strides, box, es,
        CU_TENSOR_MAP_INTERLEAVE_NONE, swz, CU_TENSOR_MAP_L2_PROMOTION_NONE, CU_TENSOR_MAP_FLOAT_OOB_FILL_NONE);
}

extern "C" void kernel_launch(void* const* d_in, const int* in_sizes, int n_in, void* d_out, int out_size) {
    (void)in_sizes; (void)n_in; (void)out_size;
    static Params prm;
    static const void* cached[8] = {nullptr};
    static int mode = -1;
    bool same = (mode >= 0) && cached[7] == d_out;
    for (int i = 0; i < 7 && same; i++) same = cached[i] == d_in[i];
    if (!same) {
        void* fn = nullptr; cudaDriverEntryPointQueryResult qr;
        cudaGetDriverEntryPoint("cuTensorMapEncodeTiled", &fn, cudaEnableDefault, &qr);
        EncodeFn enc = (EncodeFn)fn;
        void *a_x1, *a_kv;
        cudaGetSymbolAddress(&a_x1, g_x1); cudaGetSymbolAddress(&a_kv, g_kv);
        {
            cuuint64_t d[5] = {384, 2, 4, 2, 64};
            cuuint64_t s[4] = {256ull * 768, 768, 2ull * 256 * 768, 4ull * 768};
            cuuint32_t b4[5] = {64, 2, 4, 2, 4};
            encode_map(enc, &prm.tm_x, d_in[0], 5, d, s, b4, CU_TENSOR_MAP_SWIZZLE_128B);
            encode_map(enc, &prm.tm_x1s, a_x1, 5, d, s, b4, CU_TENSOR_MAP_SWIZZLE_128B);
            cuuint64_t d2[5] = {768, 2, 4, 2, 64};
            cuuint64_t s2[4] = {256ull * 1536, 1536, 2ull * 256 * 1536, 4ull * 1536};
            encode_map(enc, &prm.tm_kvs, a_kv, 5, d2, s2, b4, CU_TENSOR_MAP_SWIZZLE_128B);
        }
        {
            cuuint64_t d[2] = {384, 1024}; cuuint64_t s[1] = {768};
            cuuint32_t b[2] = {64, 64}, bo[2] = {64, 16};
            encode_map(enc, &prm.tm_x1l, a_x1, 2, d, s, b, CU_TENSOR_MAP_SWIZZLE_128B);
            encode_map(enc, &prm.tm_out, d_out, 2, d, s, bo, CU_TENSOR_MAP_SWIZZLE_128B);
        }
        {
            cuuint64_t d[3] = {32, 1024, 24}; cuuint64_t s[2] = {1536, 64};
            cuuint32_t b[3] = {32, 128, 3};
            encode_map(enc, &prm.tm_kvl, a_kv, 3, d, s, b, CU_TENSOR_MAP_SWIZZLE_64B);
        }
        const int wn[6] = {1152, 384, 1152, 384, 1536, 384}, wk[6] = {384, 384, 384, 384, 384, 1536};
        for (int i = 0; i < 6; i++) {
            cuuint64_t d[2] = {(cuuint64_t)wn[i], (cuuint64_t)wk[i]}; cuuint64_t s[1] = {(cuuint64_t)wn[i] * 2};
            cuuint32_t b[2] = {64, 64};
            encode_map(enc, &prm.tm_w[i], d_in[1 + i], 2, d, s, b, CU_TENSOR_MAP_SWIZZLE_128B);
            prm.wptr[i] = d_in[1 + i];
        }
        for (int c = 0; c < 6; c++) {
            int n = 0;
            for (int u = 0; u < 48; u++) {
                if (c >= 4 && u >= 15 && u < 21) continue;
                if (u >= 30 && u < 33) continue;
                int m, x0, y0, mode, gate = 0;
                if (u < 6) { m = 0; x0 = 64 * c; y0 = 64 * u; mode = 0; }
                else if (u < 9) { m = 1; x0 = 64 * c; y0 = 128 * (u - 6); mode = 1; }
                else if (u < 15) { m = 2; x0 = 384 + 128 * c; y0 = 64 * (u - 9); mode = 2; gate = (u == 9 || u == 10) ? 1 : 0; }
                else if (u < 21) { m = 2; x0 = 96 * c; y0 = 64 * (u - 15); mode = 2; }
                else if (u < 24) { m = 3; x0 = 64 * c; y0 = 128 * (u - 21); mode = 1; gate = (c < 4 && (u == 21 || u == 22)) ? 2 : 0; }
                else if (u < 36) { const int hh = (u - 24) / 6, j = (u - 24) % 6; m = 4; x0 = 256 * c + 128 * hh; y0 = 64 * j; mode = 2; }
                else {
                    const int pass = (u - 36) / 6, i = (u - 36) % 6;
                    const int kk = pass ? i : (i < 3 ? 2 * i : 2 * (i - 3) + 1);
                    const int hh = pass ? 1 - (kk & 1) : (kk & 1);
                    m = 5; x0 = 64 * ((c + 1 + kk) % 6); y0 = 256 * c + 128 * hh; mode = 1;
                }
                prm.stage[c][n++] = (uint32_t)x0 | ((uint32_t)y0 << 11) | ((uint32_t)m << 22) | ((uint32_t)mode << 25) | ((uint32_t)gate << 27);
            }
        }
        cudaFuncSetAttribute(fused_kernel<3>, cudaFuncAttributeMaxDynamicSharedMemorySize, SM_TOTAL);
        cudaFuncSetAttribute(fused_kernel<1>, cudaFuncAttributeMaxDynamicSharedMemorySize, SM_TOTAL);
        cudaFuncSetAttribute(fused_kernel<2>, cudaFuncAttributeMaxDynamicSharedMemorySize, SM_TOTAL);
        cudaLaunchConfig_t cfg = {};
        cfg.gridDim = dim3(NCL * CS); cfg.blockDim = dim3(NTHREADS); cfg.dynamicSmemBytes = SM_TOTAL;
        cudaLaunchAttribute at[1];
        at[0].id = cudaLaunchAttributeClusterDimension; at[0].val.clusterDim.x = CS; at[0].val.clusterDim.y = 1; at[0].val.clusterDim.z = 1;
        cfg.attrs = at; cfg.numAttrs = 1;
        int ncl = 0;
        cudaOccupancyMaxActiveClusters(&ncl, fused_kernel<3>, &cfg);
        mode = (ncl >= NCL) ? 3 : 0;
        for (int i = 0; i < 7; i++) cached[i] = d_in[i];
        cached[7] = d_out;
    }
    cudaLaunchConfig_t cfg = {};
    cfg.gridDim = dim3(NCL * CS); cfg.blockDim = dim3(NTHREADS); cfg.dynamicSmemBytes = SM_TOTAL; cfg.stream = cudaStreamPerThread;
    cudaLaunchAttribute at[1];
    at[0].id = cudaLaunchAttributeClusterDimension; at[0].val.clusterDim.x = CS; at[0].val.clusterDim.y = 1; at[0].val.clusterDim.z = 1;
    cfg.attrs = at; cfg.numAttrs = 1;
    if (mode == 3) {
        cudaLaunchKernelEx(&cfg, fused_kernel<3>, prm);
    } else {
        cudaLaunchKernelEx(&cfg, fused_kernel<1>, prm);
        cudaLaunchKernelEx(&cfg, fused_kernel<2>, prm);
    }
}
```

```cpp
#include <cuda_runtime.h>
#include <cuda_bf16.h>
#include <cuda.h>
#include <stdint.h>

namespace {

constexpr int CS = 6;
constexpr int NCL = 16;
constexpr int NTHREADS = 384;

constexpr uint32_t SM_A0 = 0;
constexpr uint32_t SM_A1 = 49152;
constexpr uint32_t SM_RING = 98304;
constexpr uint32_t SLOT = 16384;
constexpr uint32_t SM_STG = 196608;
constexpr uint32_t SM_RES = 212992;
constexpr uint32_t SM_SC = 221184;
constexpr uint32_t SM_ST = 227328;
constexpr uint32_t SM_ML = 230400;
constexpr uint32_t SM_BAR = 231424;
constexpr uint32_t SM_TOTAL = 232448;

enum {
    B_FULL = 0, B_EMPTY = 6, B_X = 12, B_SC, B_ST2, B_A0FREE, B_X1P, B_QDONE,
    B_K0, B_K0B, B_K0C, B_K1, B_V0, B_V1, B_KFREE, B_ST3, B_LAND, B_PART, B_PART_LAST = B_PART + 4, B_DONE, B_X1ST, B_KVST, B_STGFREE, B_VW, B_VFREE, B_A1FREE, B_W1X, B_KVISS, B_X1C, B_X1C_LAST = B_X1C + 5, B_X2C, B_X2C_LAST = B_X2C + 5, B_OTC, B_OTC_LAST = B_OTC + 5, B_OSH, B_OSH_LAST = B_OSH + 3, B_X1PC, B_X1PC_LAST = B_X1PC + 5, B_X1PISS, B_X1PUB, B_EPOCH, B_COUNT
};

struct Params {
    CUtensorMap tm_x;
    CUtensorMap tm_x1s;
    CUtensorMap tm_x1l;
    CUtensorMap tm_kvs;
    CUtensorMap tm_kvl;
    CUtensorMap tm_kvl1;
    CUtensorMap tm_w[7];
    const void* wptr[6];
    void* out;
    uint32_t stage[6][54];
};

__device__ __align__(1024) uint8_t g_x1[1024 * 384 * 2];
__device__ __align__(1024) uint8_t g_kv[1024 * 768 * 2];
constexpr uint32_t IMG_OT = 0, IMG_X1 = NCL * CS * 12288, IMG_X2 = 2 * NCL * CS * 12288, IMG_OS = 3 * NCL * CS * 12288;
__device__ __align__(1024) uint8_t g_img[4 * NCL * CS * 12288];
__device__ __align__(128) float2 g_part[NCL * 4 * 6 * 16];
__device__ __align__(128) unsigned g_cnt[8 * 32];
__device__ unsigned g_epoch;

__device__ __forceinline__ uint32_t smem_u32(const void* p) { return (uint32_t)__cvta_generic_to_shared(p); }
__device__ __forceinline__ void mbar_init(uint32_t bar, uint32_t cnt) { asm volatile("mbarrier.init.shared::cta.b64 [%0], %1;" :: "r"(bar), "r"(cnt) : "memory"); }
__device__ __forceinline__ void mbar_expect_tx(uint32_t bar, uint32_t bytes) { asm volatile("mbarrier.arrive.expect_tx.shared::cta.b64 _, [%0], %1;" :: "r"(bar), "r"(bytes) : "memory"); }
__device__ __forceinline__ void mbar_arrive(uint32_t bar) { asm volatile("mbarrier.arrive.shared::cta.b64 _, [%0];" :: "r"(bar) : "memory"); }
__device__ __forceinline__ void mbar_arrive_remote(uint32_t bar_cluster) { asm volatile("mbarrier.arrive.shared::cluster.b64 _, [%0];" :: "r"(bar_cluster) : "memory"); }
__device__ __forceinline__ uint32_t mbar_try(uint32_t bar, uint32_t parity) {
    uint32_t done;
    asm volatile("{\n.reg .pred p;\nmbarrier.try_wait.parity.shared::cta.b64 p, [%1], %2;\nselp.u32 %0, 1, 0, p;\n}" : "=r"(done) : "r"(bar), "r"(parity) : "memory");
    return done;
}
__device__ __forceinline__ uint32_t mbar_try_cl(uint32_t bar, uint32_t parity) {
    uint32_t done;
    asm volatile("{\n.reg .pred p;\nmbarrier.try_wait.parity.acquire.cluster.shared::cta.b64 p, [%1], %2;\nselp.u32 %0, 1, 0, p;\n}" : "=r"(done) : "r"(bar), "r"(parity) : "memory");
    return done;
}
__device__ __forceinline__ void mbar_wait(uint32_t bar, uint32_t parity) { while (!mbar_try(bar, parity)) {} }
__device__ __forceinline__ void mbar_wait_cl(uint32_t bar, uint32_t parity) { while (!mbar_try_cl(bar, parity)) {} }
constexpr long long TIMEOUT_CYC = 2000000000ll;
__device__ __forceinline__ void mbar_wait_trap(uint32_t bar, uint32_t parity) {
    if (mbar_try(bar, parity)) return;
    const long long t0 = clock64();
    while (!mbar_try(bar, parity)) { if (clock64() - t0 > TIMEOUT_CYC) __trap(); }
}
__device__ __forceinline__ uint32_t mapa(uint32_t a, uint32_t r) { uint32_t o; asm("mapa.shared::cluster.u32 %0, %1, %2;" : "=r"(o) : "r"(a), "r"(r)); return o; }
__device__ __forceinline__ bool elect_one() {
    uint32_t pred;
    asm volatile("{\n.reg .pred p;\nelect.sync _|p, 0xffffffff;\nselp.u32 %0, 1, 0, p;\n}" : "=r"(pred));
    return pred != 0;
}
__device__ __forceinline__ void bar_sync(int id, int n) { asm volatile("bar.sync %0, %1;" :: "r"(id), "r"(n) : "memory"); }
__device__ __forceinline__ void bar_arrive(int id, int n) { asm volatile("bar.arrive %0, %1;" :: "r"(id), "r"(n) : "memory"); }
__device__ __forceinline__ void fence_async_smem() { asm volatile("fence.proxy.async.shared::cta;" ::: "memory"); }
__device__ __forceinline__ void tma_ld2(uint32_t dst, const CUtensorMap* tm, int c0, int c1, uint32_t bar) {
    asm volatile("cp.async.bulk.tensor.2d.shared::cluster.global.mbarrier::complete_tx::bytes [%0], [%1, {%3, %4}], [%2];"
        :: "r"(dst), "l"(tm), "r"(bar), "r"(c0), "r"(c1) : "memory");
}
__device__ __forceinline__ void tma_ld3(uint32_t dst, const CUtensorMap* tm, int c0, int c1, int c2, uint32_t bar) {
    asm volatile("cp.async.bulk.tensor.3d.shared::cluster.global.mbarrier::complete_tx::bytes [%0], [%1, {%3, %4, %5}], [%2];"
        :: "r"(dst), "l"(tm), "r"(bar), "r"(c0), "r"(c1), "r"(c2) : "memory");
}
__device__ __forceinline__ void tma_ld5(uint32_t dst, const CUtensorMap* tm, int c0, int c1, int c2, int c3, int c4, uint32_t bar) {
    asm volatile("cp.async.bulk.tensor.5d.shared::cluster.global.mbarrier::complete_tx::bytes [%0], [%1, {%3, %4, %5, %6, %7}], [%2];"
        :: "r"(dst), "l"(tm), "r"(bar), "r"(c0), "r"(c1), "r"(c2), "r"(c3), "r"(c4) : "memory");
}
__device__ __forceinline__ void tma_st5(const CUtensorMap* tm, int c0, int c1, int c2, int c3, int c4, uint32_t src) {
    asm volatile("cp.async.bulk.tensor.5d.global.shared::cta.bulk_group [%0, {%2, %3, %4, %5, %6}], [%1];"
        :: "l"(tm), "r"(src), "r"(c0), "r"(c1), "r"(c2), "r"(c3), "r"(c4) : "memory");
}
__device__ __forceinline__ void bulk_s2g(void* dst, uint32_t src, uint32_t bytes) {
    asm volatile("cp.async.bulk.global.shared::cta.bulk_group [%0], [%1], %2;" :: "l"(dst), "r"(src), "r"(bytes) : "memory");
}
__device__ __forceinline__ void bulk_g2s_mc(uint32_t dst, const void* src, uint32_t bytes, uint32_t bar, uint16_t mask) {
    asm volatile("cp.async.bulk.shared::cluster.global.mbarrier::complete_tx::bytes.multicast::cluster [%0], [%1], %2, [%3], %4;"
        :: "r"(dst), "l"(src), "r"(bytes), "r"(bar), "h"(mask) : "memory");
}
__device__ __forceinline__ void bulk_g2s(uint32_t dst, const void* src, uint32_t bytes, uint32_t bar) {
    asm volatile("cp.async.bulk.shared::cluster.global.mbarrier::complete_tx::bytes [%0], [%1], %2, [%3];" :: "r"(dst), "l"(src), "r"(bytes), "r"(bar) : "memory");
}
__device__ __forceinline__ void bulk_commit() { asm volatile("cp.async.bulk.commit_group;" ::: "memory"); }
template <int N> __device__ __forceinline__ void bulk_wait() { asm volatile("cp.async.bulk.wait_group %0;" :: "n"(N) : "memory"); }
__device__ __forceinline__ void bulk_prefetch(const void* src, uint32_t bytes) { asm volatile("cp.async.bulk.prefetch.L2.global [%0], %1;" :: "l"(src), "r"(bytes) : "memory"); }
__device__ __forceinline__ void st_async_v4(uint32_t dst, uint32_t a, uint32_t b, uint32_t c, uint32_t d, uint32_t bar) {
    asm volatile("st.async.shared::cluster.mbarrier::complete_tx::bytes.v4.b32 [%0], {%1, %2, %3, %4}, [%5];"
        :: "r"(dst), "r"(a), "r"(b), "r"(c), "r"(d), "r"(bar) : "memory");
}
__device__ __forceinline__ void st_async_v2(uint32_t dst, uint32_t a, uint32_t b, uint32_t bar) {
    asm volatile("st.async.shared::cluster.mbarrier::complete_tx::bytes.v2.b32 [%0], {%1, %2}, [%3];"
        :: "r"(dst), "r"(a), "r"(b), "r"(bar) : "memory");
}
__device__ __forceinline__ void ldsm4(uint32_t addr, uint32_t& r0, uint32_t& r1, uint32_t& r2, uint32_t& r3) {
    asm volatile("ldmatrix.sync.aligned.m8n8.x4.shared.b16 {%0, %1, %2, %3}, [%4];" : "=r"(r0), "=r"(r1), "=r"(r2), "=r"(r3) : "r"(addr) : "memory");
}
__device__ __forceinline__ void stsm4(uint32_t addr, uint32_t r0, uint32_t r1, uint32_t r2, uint32_t r3) {
    asm volatile("stmatrix.sync.aligned.m8n8.x4.shared.b16 [%0], {%1, %2, %3, %4};" :: "r"(addr), "r"(r0), "r"(r1), "r"(r2), "r"(r3) : "memory");
}
extern __shared__ __align__(1024) uint8_t smem[];
template <class T> __device__ __forceinline__ T& sm_at(uint32_t off) { return *reinterpret_cast<T*>(smem + off); }
__device__ __forceinline__ uint32_t pack_bf16(float lo, float hi) { uint32_t r; asm("cvt.rn.bf16x2.f32 %0, %1, %2;" : "=r"(r) : "f"(hi), "f"(lo)); return r; }
__device__ __forceinline__ float bf_lo(uint32_t v) { return __uint_as_float(v << 16); }
__device__ __forceinline__ float bf_hi(uint32_t v) { return __uint_as_float(v & 0xffff0000u); }
__device__ __forceinline__ float ex2(float x) { float y; asm("ex2.approx.ftz.f32 %0, %1;" : "=f"(y) : "f"(x)); return y; }
__device__ __forceinline__ float tanh_ap(float x) { float y; asm volatile("tanh.approx.f32 %0, %1;" : "=f"(y) : "f"(x)); return y; }
__device__ __forceinline__ float ex2v(float x) { float y; asm volatile("ex2.approx.ftz.f32 %0, %1;" : "=f"(y) : "f"(x)); return y; }
__device__ __forceinline__ void wg_fence() { asm volatile("wgmma.fence.sync.aligned;" ::: "memory"); }
__device__ __forceinline__ void wg_commit() { asm volatile("wgmma.commit_group.sync.aligned;" ::: "memory"); }
template <int N> __device__ __forceinline__ void wg_wait() { asm volatile("wgmma.wait_group.sync.aligned %0;" :: "n"(N) : "memory"); }
template <int N> __device__ __forceinline__ void pin_f(float (&d)[N]) {
#pragma unroll
    for (int i = 0; i < N; i++) asm volatile("" : "+f"(d[i]) :: "memory");
}
template <int N> __device__ __forceinline__ void pin_r(uint32_t (&d)[N]) {
#pragma unroll
    for (int i = 0; i < N; i++) asm volatile("" : "+r"(d[i]) :: "memory");
}
__device__ __forceinline__ uint32_t hadd2_bf(uint32_t a, uint32_t b) { uint32_t r; asm("add.rn.bf16x2 %0, %1, %2;" : "=r"(r) : "r"(a), "r"(b)); return r; }
__device__ __forceinline__ uint32_t movm(uint32_t a) { uint32_t r; asm volatile("movmatrix.sync.aligned.m8n8.trans.b16 %0, %1;" : "=r"(r) : "r"(a)); return r; }
__device__ __forceinline__ void mma16816(float (&d)[4], uint32_t a0, uint32_t a1, uint32_t a2, uint32_t a3, uint32_t b0, uint32_t b1) {
    asm volatile("mma.sync.aligned.m16n8k16.row.col.f32.bf16.bf16.f32 {%0, %1, %2, %3}, {%4, %5, %6, %7}, {%8, %9}, {%0, %1, %2, %3};"
        : "+f"(d[0]), "+f"(d[1]), "+f"(d[2]), "+f"(d[3]) : "r"(a0), "r"(a1), "r"(a2), "r"(a3), "r"(b0), "r"(b1));
}
__device__ __forceinline__ void mma16816p(float* d, uint32_t a0, uint32_t a1, uint32_t a2, uint32_t a3, uint32_t b0, uint32_t b1) {
    asm volatile("mma.sync.aligned.m16n8k16.row.col.f32.bf16.bf16.f32 {%0, %1, %2, %3}, {%4, %5, %6, %7}, {%8, %9}, {%0, %1, %2, %3};"
        : "+f"(d[0]), "+f"(d[1]), "+f"(d[2]), "+f"(d[3]) : "r"(a0), "r"(a1), "r"(a2), "r"(a3), "r"(b0), "r"(b1));
}
__device__ __forceinline__ void wgmma_rs_n128(float (&d)[64], uint32_t a0, uint32_t a1, uint32_t a2, uint32_t a3, uint64_t db, int sd) {
    asm volatile("{\n.reg .pred p;\nsetp.ne.b32 p, %69, 0;\n"
        "wgmma.mma_async.sync.aligned.m64n128k16.f32.bf16.bf16 {%0, %1, %2, %3, %4, %5, %6, %7, %8, %9, %10, %11, %12, %13, %14, %15, %16, %17, %18, %19, %20, %21, %22, %23, %24, %25, %26, %27, %28, %29, %30, %31, %32, %33, %34, %35, %36, %37, %38, %39, %40, %41, %42, %43, %44, %45, %46, %47, %48, %49, %50, %51, %52, %53, %54, %55, %56, %57, %58, %59, %60, %61, %62, %63}, {%64, %65, %66, %67}, %68, p, 1, 1, 1;\n}\n"
        : "+f"(d[0]), "+f"(d[1]), "+f"(d[2]), "+f"(d[3]), "+f"(d[4]), "+f"(d[5]), "+f"(d[6]), "+f"(d[7]), "+f"(d[8]), "+f"(d[9]), "+f"(d[10]), "+f"(d[11]), "+f"(d[12]), "+f"(d[13]), "+f"(d[14]), "+f"(d[15]), "+f"(d[16]), "+f"(d[17]), "+f"(d[18]), "+f"(d[19]), "+f"(d[20]), "+f"(d[21]), "+f"(d[22]), "+f"(d[23]), "+f"(d[24]), "+f"(d[25]), "+f"(d[26]), "+f"(d[27]), "+f"(d[28]), "+f"(d[29]), "+f"(d[30]), "+f"(d[31]), "+f"(d[32]), "+f"(d[33]), "+f"(d[34]), "+f"(d[35]), "+f"(d[36]), "+f"(d[37]), "+f"(d[38]), "+f"(d[39]), "+f"(d[40]), "+f"(d[41]), "+f"(d[42]), "+f"(d[43]), "+f"(d[44]), "+f"(d[45]), "+f"(d[46]), "+f"(d[47]), "+f"(d[48]), "+f"(d[49]), "+f"(d[50]), "+f"(d[51]), "+f"(d[52]), "+f"(d[53]), "+f"(d[54]), "+f"(d[55]), "+f"(d[56]), "+f"(d[57]), "+f"(d[58]), "+f"(d[59]), "+f"(d[60]), "+f"(d[61]), "+f"(d[62]), "+f"(d[63])
        : "r"(a0), "r"(a1), "r"(a2), "r"(a3), "l"(db), "r"(sd));
}

__device__ __forceinline__ void wgmma_rs_n96(float (&d)[48], uint32_t a0, uint32_t a1, uint32_t a2, uint32_t a3, uint64_t db, int sd) {
    asm volatile("{\n.reg .pred p;\nsetp.ne.b32 p, %53, 0;\n"
        "wgmma.mma_async.sync.aligned.m64n96k16.f32.bf16.bf16 {%0, %1, %2, %3, %4, %5, %6, %7, %8, %9, %10, %11, %12, %13, %14, %15, %16, %17, %18, %19, %20, %21, %22, %23, %24, %25, %26, %27, %28, %29, %30, %31, %32, %33, %34, %35, %36, %37, %38, %39, %40, %41, %42, %43, %44, %45, %46, %47}, {%48, %49, %50, %51}, %52, p, 1, 1, 1;\n}\n"
        : "+f"(d[0]), "+f"(d[1]), "+f"(d[2]), "+f"(d[3]), "+f"(d[4]), "+f"(d[5]), "+f"(d[6]), "+f"(d[7]), "+f"(d[8]), "+f"(d[9]), "+f"(d[10]), "+f"(d[11]), "+f"(d[12]), "+f"(d[13]), "+f"(d[14]), "+f"(d[15]), "+f"(d[16]), "+f"(d[17]), "+f"(d[18]), "+f"(d[19]), "+f"(d[20]), "+f"(d[21]), "+f"(d[22]), "+f"(d[23]), "+f"(d[24]), "+f"(d[25]), "+f"(d[26]), "+f"(d[27]), "+f"(d[28]), "+f"(d[29]), "+f"(d[30]), "+f"(d[31]), "+f"(d[32]), "+f"(d[33]), "+f"(d[34]), "+f"(d[35]), "+f"(d[36]), "+f"(d[37]), "+f"(d[38]), "+f"(d[39]), "+f"(d[40]), "+f"(d[41]), "+f"(d[42]), "+f"(d[43]), "+f"(d[44]), "+f"(d[45]), "+f"(d[46]), "+f"(d[47])
        : "r"(a0), "r"(a1), "r"(a2), "r"(a3), "l"(db), "r"(sd));
}

__device__ __forceinline__ void wgmma_rs_n64(float (&d)[32], uint32_t a0, uint32_t a1, uint32_t a2, uint32_t a3, uint64_t db, int sd) {
    asm volatile("{\n.reg .pred p;\nsetp.ne.b32 p, %37, 0;\n"
        "wgmma.mma_async.sync.aligned.m64n64k16.f32.bf16.bf16 {%0, %1, %2, %3, %4, %5, %6, %7, %8, %9, %10, %11, %12, %13, %14, %15, %16, %17, %18, %19, %20, %21, %22, %23, %24, %25, %26, %27, %28, %29, %30, %31}, {%32, %33, %34, %35}, %36, p, 1, 1, 1;\n}\n"
        : "+f"(d[0]), "+f"(d[1]), "+f"(d[2]), "+f"(d[3]), "+f"(d[4]), "+f"(d[5]), "+f"(d[6]), "+f"(d[7]), "+f"(d[8]), "+f"(d[9]), "+f"(d[10]), "+f"(d[11]), "+f"(d[12]), "+f"(d[13]), "+f"(d[14]), "+f"(d[15]), "+f"(d[16]), "+f"(d[17]), "+f"(d[18]), "+f"(d[19]), "+f"(d[20]), "+f"(d[21]), "+f"(d[22]), "+f"(d[23]), "+f"(d[24]), "+f"(d[25]), "+f"(d[26]), "+f"(d[27]), "+f"(d[28]), "+f"(d[29]), "+f"(d[30]), "+f"(d[31])
        : "r"(a0), "r"(a1), "r"(a2), "r"(a3), "l"(db), "r"(sd));
}

__device__ __forceinline__ void wgmma_ss_n64(float (&d)[32], uint64_t da, uint64_t db, int sd) {
    asm volatile("{\n.reg .pred p;\nsetp.ne.b32 p, %34, 0;\n"
        "wgmma.mma_async.sync.aligned.m64n64k16.f32.bf16.bf16 {%0, %1, %2, %3, %4, %5, %6, %7, %8, %9, %10, %11, %12, %13, %14, %15, %16, %17, %18, %19, %20, %21, %22, %23, %24, %25, %26, %27, %28, %29, %30, %31}, %32, %33, p, 1, 1, 0, 1;\n}\n"
        : "+f"(d[0]), "+f"(d[1]), "+f"(d[2]), "+f"(d[3]), "+f"(d[4]), "+f"(d[5]), "+f"(d[6]), "+f"(d[7]), "+f"(d[8]), "+f"(d[9]), "+f"(d[10]), "+f"(d[11]), "+f"(d[12]), "+f"(d[13]), "+f"(d[14]), "+f"(d[15]), "+f"(d[16]), "+f"(d[17]), "+f"(d[18]), "+f"(d[19]), "+f"(d[20]), "+f"(d[21]), "+f"(d[22]), "+f"(d[23]), "+f"(d[24]), "+f"(d[25]), "+f"(d[26]), "+f"(d[27]), "+f"(d[28]), "+f"(d[29]), "+f"(d[30]), "+f"(d[31])
        : "l"(da), "l"(db), "r"(sd));
}

__device__ __forceinline__ void wgmma_ss_n128_bn(float (&d)[64], uint64_t da, uint64_t db, int sd) {
    asm volatile("{\n.reg .pred p;\nsetp.ne.b32 p, %66, 0;\n"
        "wgmma.mma_async.sync.aligned.m64n128k16.f32.bf16.bf16 {%0, %1, %2, %3, %4, %5, %6, %7, %8, %9, %10, %11, %12, %13, %14, %15, %16, %17, %18, %19, %20, %21, %22, %23, %24, %25, %26, %27, %28, %29, %30, %31, %32, %33, %34, %35, %36, %37, %38, %39, %40, %41, %42, %43, %44, %45, %46, %47, %48, %49, %50, %51, %52, %53, %54, %55, %56, %57, %58, %59, %60, %61, %62, %63}, %64, %65, p, 1, 1, 0, 0;\n}\n"
        : "+f"(d[0]), "+f"(d[1]), "+f"(d[2]), "+f"(d[3]), "+f"(d[4]), "+f"(d[5]), "+f"(d[6]), "+f"(d[7]), "+f"(d[8]), "+f"(d[9]), "+f"(d[10]), "+f"(d[11]), "+f"(d[12]), "+f"(d[13]), "+f"(d[14]), "+f"(d[15]), "+f"(d[16]), "+f"(d[17]), "+f"(d[18]), "+f"(d[19]), "+f"(d[20]), "+f"(d[21]), "+f"(d[22]), "+f"(d[23]), "+f"(d[24]), "+f"(d[25]), "+f"(d[26]), "+f"(d[27]), "+f"(d[28]), "+f"(d[29]), "+f"(d[30]), "+f"(d[31]), "+f"(d[32]), "+f"(d[33]), "+f"(d[34]), "+f"(d[35]), "+f"(d[36]), "+f"(d[37]), "+f"(d[38]), "+f"(d[39]), "+f"(d[40]), "+f"(d[41]), "+f"(d[42]), "+f"(d[43]), "+f"(d[44]), "+f"(d[45]), "+f"(d[46]), "+f"(d[47]), "+f"(d[48]), "+f"(d[49]), "+f"(d[50]), "+f"(d[51]), "+f"(d[52]), "+f"(d[53]), "+f"(d[54]), "+f"(d[55]), "+f"(d[56]), "+f"(d[57]), "+f"(d[58]), "+f"(d[59]), "+f"(d[60]), "+f"(d[61]), "+f"(d[62]), "+f"(d[63])
        : "l"(da), "l"(db), "r"(sd));
}


__device__ __forceinline__ constexpr uint32_t bar_count(int i) {
    return ((i >= B_EMPTY && i < B_EMPTY + 6) || i == B_A0FREE || i == B_QDONE || i == B_X1ST || i == B_KVST || i == B_A1FREE) ? 4
         : i == B_KFREE ? 48 : i == B_LAND ? 20 : i == B_DONE ? 8 : i == B_VFREE ? 24 : 1;
}
__device__ __forceinline__ constexpr uint32_t bar_tx(int i) {
    return i == B_SC ? 6144 : (i >= B_PART && i <= B_PART_LAST) ? 8192 : (i == B_ST2 || i == B_ST3) ? 3072 : 0;
}
__device__ __forceinline__ uint32_t bar_addr(uint32_t sb, int b) { return sb + SM_BAR + b * 8; }

struct RingPos { uint32_t slot, par; };
__device__ __forceinline__ RingPos ring_pos(uint32_t s) { const uint32_t q = (s * 43u) >> 8; RingPos r; r.slot = s - 6u * q; r.par = q & 1u; return r; }
__device__ __forceinline__ void ring_adv(RingPos& r, uint32_t stride) { r.slot += stride; if (r.slot >= 6u) { r.slot -= 6u; r.par ^= 1u; } }
__device__ __forceinline__ void ring_release(uint32_t sb, uint32_t slot, int lane) { if (lane == 0) mbar_arrive(sb + SM_BAR + (B_EMPTY + slot) * 8); }
__device__ __forceinline__ void ring_wait(uint32_t sb, const RingPos& r) { mbar_wait(sb + SM_BAR + (B_FULL + r.slot) * 8, r.par); }
constexpr uint32_t DHI_B = (1024u >> 4) | (1u << 30);
constexpr uint32_t DHI_64 = (512u >> 4) | (2u << 30);
__device__ __forceinline__ uint64_t mkd(uint32_t addr, uint32_t lbo, uint32_t hi) {
    return ((uint64_t)hi << 32) | (uint64_t)(((addr & 0x3FFFF) >> 4) | ((lbo >> 4) << 16));
}
constexpr uint32_t ONES2 = 0x3F803F80u;

__device__ __forceinline__ void finish_stats(float s0, float q0, float s1, float q1, uint32_t& nm0, uint32_t& nm1, float& r0, float& r1) {
    const float m0 = s0 * (1.f / 384.f), m1 = s1 * (1.f / 384.f);
    r0 = rsqrtf(fmaxf(q0 * (1.f / 384.f) - m0 * m0, 0.f) + 1e-5f);
    r1 = rsqrtf(fmaxf(q1 * (1.f / 384.f) - m1 * m1, 0.f) + 1e-5f);
    nm0 = pack_bf16(-m0, -m0); nm1 = pack_bf16(-m1, -m1);
}
template <int PSTRIDE, int R8>
__device__ __forceinline__ void combine_stats(uint32_t a, uint32_t& nm0, uint32_t& nm1, float& r0, float& r1) {
    float2 u[6], v[6];
#pragma unroll
    for (int i = 0; i < 6; i++) { u[i] = sm_at<float2>(a + i * PSTRIDE); v[i] = sm_at<float2>(a + i * PSTRIDE + R8); }
    const float s0 = ((u[0].x + u[1].x) + (u[2].x + u[3].x)) + (u[4].x + u[5].x), q0 = ((u[0].y + u[1].y) + (u[2].y + u[3].y)) + (u[4].y + u[5].y);
    const float s1 = ((v[0].x + v[1].x) + (v[2].x + v[3].x)) + (v[4].x + v[5].x), q1 = ((v[0].y + v[1].y) + (v[2].y + v[3].y)) + (v[4].y + v[5].y);
    finish_stats(s0, q0, s1, q1, nm0, nm1, r0, r1);
}

template <int N> __device__ __forceinline__ void wgmma_rs(float (&acc)[N / 2], const uint32_t* f, uint64_t db, int sd) {
    if constexpr (N == 128) wgmma_rs_n128(acc, f[0], f[1], f[2], f[3], db, sd);
    else if constexpr (N == 96) wgmma_rs_n96(acc, f[0], f[1], f[2], f[3], db, sd);
    else wgmma_rs_n64(acc, f[0], f[1], f[2], f[3], db, sd);
}
template <int N, int CPS, bool MEAN, bool FIXED = false, bool XTRA = false, bool PRE = false, int XB = -1>
__device__ __forceinline__ void gemm_rs(float (&acc)[N / 2], uint32_t sb, uint32_t a, uint32_t nm0, uint32_t nm1,
                                        uint32_t s0, uint32_t stride, int lane, int arrive_bar, bool xw = false, int sync_bar = -1, int rot = 0) {
    uint32_t f[6][16];
    if (MEAN) {
        float s[4][4];
#pragma unroll
        for (int ks = 0; ks < 4; ks++) { s[ks][0] = s[ks][1] = s[ks][2] = s[ks][3] = 0.f; }
#pragma unroll
        for (int j = 0; j < 6; j++)
#pragma unroll
            for (int ks = 0; ks < 4; ks++) {
                ldsm4((a ^ (ks << 5)) + j * 8192, f[j][4 * ks], f[j][4 * ks + 1], f[j][4 * ks + 2], f[j][4 * ks + 3]);
                mma16816(s[ks], f[j][4 * ks], f[j][4 * ks + 1], f[j][4 * ks + 2], f[j][4 * ks + 3], ONES2, ONES2);
            }
        const float m0 = ((s[0][0] + s[1][0]) + (s[2][0] + s[3][0])) * (-1.f / 384.f), m1 = ((s[0][2] + s[1][2]) + (s[2][2] + s[3][2])) * (-1.f / 384.f);
        nm0 = pack_bf16(m0, m0); nm1 = pack_bf16(m1, m1);
    }
    RingPos rp = ring_pos(FIXED ? 0 : s0), rr = rp;
    auto prep = [&](int j) {
        if (!MEAN) {
            int ch = j;
            if (XB >= 0) { ch = rot + j; if (ch >= 6) ch -= 6; mbar_wait(bar_addr(sb, XB + ch), 0); }
#pragma unroll
            for (int ks = 0; ks < 4; ks++) ldsm4((a ^ (ks << 5)) + ch * 8192, f[j][4 * ks], f[j][4 * ks + 1], f[j][4 * ks + 2], f[j][4 * ks + 3]);
        }
#pragma unroll
        for (int i = 0; i < 16; i++) f[j][i] = hadd2_bf(f[j][i], (i & 1) ? nm1 : nm0);
    };
    const bool pre = XTRA ? xw : PRE;
    if (pre) {
#pragma unroll
        for (int j = 0; j < 6; j++) prep(j);
        if (sync_bar >= 0) bar_sync(sync_bar, 256);
    }
    constexpr int NG = FIXED ? 1 : (XB >= 0 ? 4 : (MEAN ? 2 : 3));
    int nrel = 0;
#pragma unroll
    for (int gq = 0; gq < NG; gq++) {
        const int j0 = FIXED ? 0 : (XB >= 0 ? (gq < 2 ? gq : 2 * gq - 2) : (MEAN ? 3 * gq : 2 * gq));
        const int j1 = FIXED ? 6 : (XB >= 0 ? (gq < 2 ? gq + 1 : 2 * gq) : (MEAN ? 3 * gq + 3 : 2 * gq + 2));
        const int n1 = gq + 1 < NG ? (XB >= 0 ? (gq + 1 < 2 ? gq + 2 : 2 * gq + 2) : (MEAN ? 6 : 2 * gq + 4)) : j1;
        uint64_t db[6];
        if (!pre && gq == 0) {
#pragma unroll
            for (int j = j0; j < j1; j++) prep(j);
        }
#pragma unroll
        for (int j = j0; j < j1; j++) {
            const bool inx = XTRA && xw && j < 3;
            if (FIXED) { if (j == 0) mbar_wait(bar_addr(sb, stride), 0); }
            else if (inx) { if (j == 0) mbar_wait(bar_addr(sb, B_W1X), 0); }
            else if (j % CPS == 0) ring_wait(sb, rp);
            db[j - j0] = FIXED ? mkd(sb + s0 + j * 8192, 8192, DHI_B)
                       : N == 96 ? mkd(sb + SM_RING + rp.slot * SLOT, 4096, DHI_64)
                               : mkd(inx ? sb + SM_A1 + j * SLOT : sb + SM_RING + rp.slot * SLOT + (j % CPS) * 8192, 8192, DHI_B);
            if (!FIXED && !inx && j % CPS == CPS - 1) ring_adv(rp, stride);
        }
        wg_fence();
#pragma unroll
        for (int j = j0; j < j1; j++)
#pragma unroll
            for (int ks = 0; ks < 4; ks++) wgmma_rs<N>(acc, &f[j][4 * ks], db[j - j0] + ks * (N == 96 ? 64 : 128), (j | ks) != 0);
        wg_commit();
        if (!pre) {
#pragma unroll
            for (int j = j1; j < n1; j++) prep(j);
        }
        if (gq == NG - 1) {
            if (arrive_bar >= 0) bar_arrive(arrive_bar, 256);
            if (MEAN) asm volatile("barrier.cluster.wait.aligned;" ::: "memory");
        }
        if (!FIXED && gq >= 1) {
            wg_wait<1>();
            const int done = j0 / CPS - ((XTRA) ? 0 : 0);
            if (!(XTRA && xw)) {
#pragma unroll
                for (int i = nrel; i < done; i++) { ring_release(sb, rr.slot, lane); ring_adv(rr, stride); }
            } else if (j0 == 4) { ring_release(sb, rr.slot, lane); ring_adv(rr, stride); }
            nrel = done;
        }
    }
    wg_wait<0>();
#pragma unroll
    for (int j = 0; j < 6; j++) pin_r(f[j]);
    pin_f(acc);
    if (!FIXED) {
#pragma unroll
        for (int i = 0; i < (MEAN ? 3 : 2 / CPS); i++) { ring_release(sb, rr.slot, lane); ring_adv(rr, stride); }
    }
}

__device__ __forceinline__ float gelu_f(float a, float A, float B, float H) {
    const float u = a * fmaf(a * a, B, A);
    const float h = a * H;
    return fmaf(tanh_ap(u), h, h);
}

__device__ __forceinline__ unsigned ld_relaxed(const unsigned* p) { unsigned v; asm volatile("ld.relaxed.gpu.global.u32 %0, [%1];" : "=r"(v) : "l"(p) : "memory"); return v; }
__device__ __forceinline__ void poll_cnt(const unsigned* p, unsigned target, int lane) {
    if (lane == 0) {
        int it = 0;
        while ((int)(ld_relaxed(p) - target) < 0) { if (++it > (1 << 22)) __trap(); }
        asm volatile("fence.proxy.async.global;" ::: "memory");
    }
    __syncwarp();
}
__device__ __forceinline__ void signal_cnt(unsigned* p) {
    asm volatile("red.relaxed.gpu.global.add.u32 [%0], 1;" :: "l"(p) : "memory");
}

template <int PH>
__device__ __forceinline__ void proj_block(uint32_t sb, uint32_t stage0, int c, int k, int lane, int ww, uint32_t a128, uint8_t* img) {
    const int g = lane >> 2, q4 = lane & 3, row0 = 16 * ww + g;
    float acc[32];
    const uint32_t own = sb + (PH ? SM_A0 : SM_A1) + c * 8192;
    const uint32_t res = PH ? sb + SM_RES : own;
    uint32_t y[16];
#pragma unroll
    for (int jj = 0; jj < 4; jj++) ldsm4(res + (a128 ^ (jj << 5)), y[4 * jj], y[4 * jj + 1], y[4 * jj + 2], y[4 * jj + 3]);
    const uint32_t sta = sb + SM_ST + c * 512 + row0 * 8, stb = bar_addr(sb, PH ? B_ST3 : B_ST2);
    const uint32_t ra0 = mapa(sta, q4), rb0 = mapa(stb, q4), ra1 = mapa(sta, (q4 & 1) + 4), rb1 = mapa(stb, (q4 & 1) + 4);
    uint8_t* gi = img + (PH ? IMG_X2 : IMG_X1) + ww * 2048;
    {
        const uint64_t da = PH ? mkd(sb + SM_A1, 16, DHI_64) : mkd(sb + SM_A0, 16, DHI_B);
        RingPos rp = ring_pos(stage0), rr = rp;
        int ch = PH ? (c < 4 ? (3 * c + 1) >> 1 : 0) : c;
#pragma unroll
        for (int jj = 0; jj < 6; jj++) {
            if (PH) { mbar_wait(bar_addr(sb, B_OSH + ((2 * ch * 11) >> 5)), 0); mbar_wait(bar_addr(sb, B_OSH + (((2 * ch + 1) * 11) >> 5)), 0); }
            else mbar_wait(bar_addr(sb, B_OTC + ch), 0);
            if ((jj & 1) == 0) ring_wait(sb, rp);
            const uint64_t db = mkd(sb + SM_RING + rp.slot * SLOT + (jj & 1) * 8192, 8192, DHI_B);
            const uint64_t dc = da + ch * 512;
            wg_fence();
#pragma unroll
            for (int ks = 0; ks < 4; ks++)
                wgmma_ss_n64(acc, dc + (PH ? (ks >> 1) * 256 + (ks & 1) * 2 : ks * 2), db + ks * 128, (jj | ks) != 0);
            wg_commit();
            if (jj & 1) ring_adv(rp, 1);
            if (jj == 2 || jj == 4) { wg_wait<1>(); ring_release(sb, rr.slot, lane); ring_adv(rr, 1); }
            if (++ch == 6) ch = 0;
        }
        wg_wait<0>();
        pin_f(acc);
        ring_release(sb, rr.slot, lane);
    }
    if (lane == 0) mbar_arrive(bar_addr(sb, PH ? B_A1FREE : B_A0FREE));
#pragma unroll
    for (int jj = 0; jj < 4; jj++)
#pragma unroll
        for (int i = 0; i < 4; i++) y[4 * jj + i] = hadd2_bf(y[4 * jj + i], pack_bf16(acc[8 * jj + 2 * i], acc[8 * jj + 2 * i + 1]));
    float sm[4] = {0.f, 0.f, 0.f, 0.f}, ga[4] = {0.f, 0.f, 0.f, 0.f}, gb[4] = {0.f, 0.f, 0.f, 0.f};
#pragma unroll
    for (int jj = 0; jj < 4; jj++) {
        mma16816(sm, y[4 * jj], y[4 * jj + 1], y[4 * jj + 2], y[4 * jj + 3], ONES2, ONES2);
        mma16816(ga, y[4 * jj], y[4 * jj + 1], y[4 * jj + 2], y[4 * jj + 3], y[4 * jj], y[4 * jj + 2]);
        mma16816(gb, y[4 * jj], y[4 * jj + 1], y[4 * jj + 2], y[4 * jj + 3], y[4 * jj + 1], y[4 * jj + 3]);
    }
#pragma unroll
    for (int jj = 0; jj < 4; jj++) stsm4(own + (a128 ^ (jj << 5)), y[4 * jj], y[4 * jj + 1], y[4 * jj + 2], y[4 * jj + 3]);
    const int src = (lane & ~3) | (g >> 1);
    const float q0 = __shfl_sync(0xffffffffu, (g & 1) ? ga[1] : ga[0], src), q1 = __shfl_sync(0xffffffffu, (g & 1) ? gb[3] : gb[2], src);
    st_async_v2(ra0, __float_as_uint(sm[0]), __float_as_uint(q0), rb0);
    st_async_v2(ra0 + 64, __float_as_uint(sm[2]), __float_as_uint(q1), rb0);
    if (q4 < 2) {
        st_async_v2(ra1, __float_as_uint(sm[0]), __float_as_uint(q0), rb1);
        st_async_v2(ra1 + 64, __float_as_uint(sm[2]), __float_as_uint(q1), rb1);
    }
    fence_async_smem();
    __syncwarp();
    const bool leader = elect_one();
    if (leader) {
        bulk_s2g(gi, own + ww * 2048, 2048); bulk_commit();
        mbar_arrive(bar_addr(sb, (PH ? B_X2C : B_X1C) + c));
    }
    if (PH) {
#pragma unroll
        for (int jj = 0; jj < 4; jj++) stsm4(res + (a128 ^ (jj << 5)), y[4 * jj], y[4 * jj + 1], y[4 * jj + 2], y[4 * jj + 3]);
    }
    if (leader) { bulk_wait<0>(); bulk_g2s_mc(own + ww * 2048, gi, 2048, bar_addr(sb, (PH ? B_X2C : B_X1C) + c), (uint16_t)(0x3F & ~(1 << c))); }
    if (PH == 0) {
        if (q4 < 2) sm_at<float2>(SM_ML + (2 * q4 + (g & 1)) * 128 + (4 * ww + (g >> 1)) * 8) = q4 ? make_float2(sm[2], q1) : make_float2(sm[0], q0);
        fence_async_smem();
        __syncwarp();
        if (lane == 0) mbar_arrive(bar_addr(sb, B_X1ST));
    }
    __syncwarp();
}

constexpr float SL2 = 0.10206207261596577f * 1.4426950408889634f;

template <int PHASES>
__global__ void __launch_bounds__(NTHREADS, 1) fused_kernel(const __grid_constant__ Params p) {
    const uint32_t sb = smem_u32(smem);
    const int tid = threadIdx.x, lane = tid & 31;
    const int warp = __shfl_sync(0xffffffffu, tid >> 5, 0);
    uint32_t c_u; asm("mov.u32 %0, %%cluster_ctarank;" : "=r"(c_u));
    const int c = (int)c_u;
    const int k = blockIdx.x / CS;
    const bool att = c < 4;
    constexpr bool P1 = (PHASES & 1) != 0, P2 = (PHASES & 2) != 0;
    constexpr int UBEG = P1 ? 0 : 15;

    if (warp == 8) {
        if (elect_one()) {
            mbar_init(bar_addr(sb, B_X), 1);
            mbar_init(bar_addr(sb, B_VW), 1);
#pragma unroll
            for (int i = 0; i < 6; i++) mbar_init(bar_addr(sb, B_FULL + i), 1);
            asm volatile("fence.mbarrier_init.release.cluster;" ::: "memory");
            fence_async_smem();
        }
        __syncwarp();
        bar_arrive(9, NTHREADS);
        if (P1 && elect_one()) {
            const uint32_t b = bar_addr(sb, B_X);
            mbar_expect_tx(b, 49152);
#pragma unroll 1
            for (int j = 0; j < 6; j++) tma_ld5(sb + SM_A1 + j * 8192, &p.tm_x, 64 * j, 0, 0, 0, 4 * k, b);
        }
        __syncwarp();
        bar_sync(10, 64);
    } else if (warp == 11) {
        if (elect_one()) {
#pragma unroll
            for (int i = B_EMPTY; i < B_X1C; i++) if (i != B_X && i != B_VW) mbar_init(bar_addr(sb, i), bar_count(i));
            mbar_init(bar_addr(sb, B_X1PISS), 1);
            mbar_init(bar_addr(sb, B_X1PUB), 1);
            mbar_init(bar_addr(sb, B_EPOCH), 1);
#pragma unroll
            for (int j = 0; j < 6; j++) {
                mbar_init(bar_addr(sb, B_X1C + j), j == c ? 4 : 1);
                mbar_init(bar_addr(sb, B_X2C + j), j == c ? 4 : 1);
                mbar_init(bar_addr(sb, B_OTC + j), j == c ? 4 : 1);
                mbar_init(bar_addr(sb, B_X1PC + j), 1);
                if (j < 4) { mbar_init(bar_addr(sb, B_OSH + j), 1); if (j != c) mbar_expect_tx(bar_addr(sb, B_OSH + j), 12288); }
                if (j != c) { mbar_expect_tx(bar_addr(sb, B_X1C + j), 8192); mbar_expect_tx(bar_addr(sb, B_X2C + j), 8192); mbar_expect_tx(bar_addr(sb, B_OTC + j), 8192); }
            }
#pragma unroll
            for (int i = B_EMPTY; i < B_X1C; i++) if (bar_tx(i)) mbar_expect_tx(bar_addr(sb, i), bar_tx(i));
            asm volatile("fence.mbarrier_init.release.cluster;" ::: "memory");
        }
        __syncwarp();
        bar_arrive(9, NTHREADS);
        bar_arrive(10, 64);
    } else {
        bar_sync(9, NTHREADS);
        if (warp == 10 && elect_one()) {
#pragma unroll 1
            for (int s = 0; s < 6; s++) {
                const uint32_t e = p.stage[c][UBEG + s];
                const int x0 = e & 2047, y0 = (e >> 11) & 2047, mode = (e >> 25) & 3;
                const CUtensorMap* tm = &p.tm_w[(e >> 22) & 7];
                const uint32_t fb = bar_addr(sb, B_FULL + s), dst = sb + SM_RING + s * SLOT;
                if (((e >> 22) & 7) == 6) { mbar_expect_tx(fb, 12288); tma_ld3(dst, tm, 0, y0, x0, fb); }
                else {
                    mbar_expect_tx(fb, SLOT);
                    tma_ld2(dst, tm, x0, y0, fb);
                    tma_ld2(dst + 8192, tm, x0 + (mode == 0 ? 384 : (mode == 2 ? 64 : 0)), mode == 1 ? y0 + 64 : (mode == 3 ? (y0 == 320 ? 0 : y0 + 64) : y0), fb);
                }
            }
        }
        __syncwarp();
    }
    asm volatile("barrier.cluster.arrive.relaxed.aligned;" ::: "memory");

    if (warp >= 8) {
        asm volatile("setmaxnreg.dec.sync.aligned.u32 40;");
        if (warp == 8 || warp == 10) {
            const int odd = warp == 10;
            const int nst = (P2 ? (att ? 45 : 39) : 15) - UBEG;
            const uint32_t* tbl = &p.stage[c][UBEG];
            uint32_t slot = odd, par = 0;
            uint32_t e = tbl[6 + odd];
#pragma unroll 1
            for (int s = 6 + odd; s < nst; s += 2) {
                const int x0 = e & 2047, y0 = (e >> 11) & 2047, mode = (e >> 25) & 3, gate = e >> 27;
                const bool q3d = ((e >> 22) & 7) == 6;
                const CUtensorMap* tm = &p.tm_w[(e >> 22) & 7];
                const int x1 = x0 + (mode == 0 ? 384 : (mode == 2 ? 64 : 0)), y1 = mode == 1 ? y0 + 64 : (mode == 3 ? (y0 == 320 ? 0 : y0 + 64) : y0);
                e = tbl[s + 2];
                const uint32_t fb = bar_addr(sb, B_FULL + slot), dst = sb + SM_RING + slot * SLOT;
                if (gate) mbar_wait_trap(bar_addr(sb, gate == 1 ? B_VFREE : (gate == 2 ? B_KVISS : B_X1PISS)), 0);
                mbar_wait_trap(bar_addr(sb, B_EMPTY + slot), par);
                if (elect_one()) {
                    if (q3d) { mbar_expect_tx(fb, 12288); tma_ld3(dst, tm, 0, y0, x0, fb); }
                    else {
                        mbar_expect_tx(fb, SLOT);
                        tma_ld2(dst, tm, x0, y0, fb);
                        tma_ld2(dst + 8192, tm, x1, y1, fb);
                    }
                }
                __syncwarp();
                slot += 2; if (slot >= 6) { slot -= 6; par ^= 1; }
            }
            if (odd) mbar_wait_trap(bar_addr(sb, B_DONE), 0);
        } else if (warp == 9) {
            unsigned epoch = 0;
            if (PHASES == 3) epoch = *(volatile unsigned*)&g_epoch;
            if (P1 && elect_one()) {
                const uint32_t b = bar_addr(sb, B_VW);
                mbar_expect_tx(b, 49152);
#pragma unroll 1
                for (int j = 0; j < 6; j++) tma_ld2(sb + SM_A0 + j * 8192, &p.tm_w[0], 768 + 64 * c, 64 * j, b);
            }
            __syncwarp();
            if (PHASES == 3) { epoch += 1; if (epoch == 0) __trap(); if (lane == 0) mbar_arrive(bar_addr(sb, B_EPOCH)); }
            if (P1) mbar_wait_trap(bar_addr(sb, B_X), 0);
            if (lane >= 1 && lane < 6) {
                const int per = (lane == 2 ? 9216 : (lane >= 4 ? 12288 : 3072));
                bulk_prefetch((const char*)p.wptr[lane] + (size_t)blockIdx.x * per, per);
            }
            if (P2) {
                const int row0 = k * 64;
                if (P1) mbar_wait_trap(bar_addr(sb, B_A0FREE), 0);
                if (PHASES == 3) poll_cnt(g_cnt + 32 * (k & 3), epoch * 24, lane);
                if (elect_one()) {
                    const uint32_t b = bar_addr(sb, B_X1P);
                    mbar_expect_tx(b, att ? 8192 + 3072 : 8192);
                    tma_ld2(sb + SM_RES, &p.tm_x1l, 64 * c, row0, b);
                    if (att) {
#pragma unroll 1
                        for (int i = 0; i < 4; i++) bulk_g2s(sb + SM_SC + i * 768, g_part + ((4 * (k & 3) + i) * 4 + (k >> 2)) * 96, 768, b);
#pragma unroll 1
                        for (int j = 0; j < 6; j++) {
                            const uint32_t bj = bar_addr(sb, B_X1PC + j);
                            mbar_expect_tx(bj, 8192);
                            tma_ld2(sb + SM_A0 + j * 8192, &p.tm_x1l, 64 * j, row0, bj);
                        }
                    }
                    mbar_arrive(bar_addr(sb, B_X1PISS));
                }
                __syncwarp();
                if (att) {
                    const int trow = (k >> 2) * 256;
                    if (P1) { mbar_wait_trap(bar_addr(sb, B_X1PUB), 0); mbar_wait_trap(bar_addr(sb, B_KVST), 0); }
                    unsigned done = 0;
                    int it = 0;
                    while (done != 15u) {
                        unsigned m = 15u;
                        if (PHASES == 3) {
                            const bool ok = lane < 4 && (int)(ld_relaxed(g_cnt + 128 + 32 * (lane & 3)) - epoch * 24) >= 0;
                            m = __ballot_sync(0xffffffffu, ok);
                            if (++it > (1 << 21)) __trap();
                        }
                        m &= ~done;
                        if (PHASES == 3 && m) asm volatile("fence.proxy.async.global;" ::: "memory");
                        if ((m & 1u) && elect_one()) {
#pragma unroll 1
                            for (int blk = 0; blk < 3; blk++) {
                                const uint32_t b = bar_addr(sb, B_K0 + blk);
                                mbar_expect_tx(b, 8192);
                                tma_ld3(sb + SM_A1 + blk * 8192, &p.tm_kvl1, 0, trow, 3 * c + blk, b);
                            }
                        }
                        if ((m & 2u) && elect_one()) {
                            const uint32_t b = bar_addr(sb, B_K1);
                            mbar_expect_tx(b, 24576);
                            tma_ld3(sb + SM_A1 + 24576, &p.tm_kvl, 0, trow + 128, 3 * c, b);
                        }
                        unsigned mv = m & 12u;
                        if (((done | m) & 3u) != 3u) { mv = 0; m &= 3u; }
                        if (mv) {
                            mbar_wait_trap(bar_addr(sb, B_QDONE), 0);
                            if ((mv & 4u) && elect_one()) {
                                const uint32_t b = bar_addr(sb, B_V0);
                                mbar_expect_tx(b, 24576);
                                tma_ld3(sb + SM_A0, &p.tm_kvl, 0, trow, 12 + 3 * c, b);
                            }
                            if ((mv & 8u) && elect_one()) {
                                const uint32_t b = bar_addr(sb, B_V1);
                                mbar_expect_tx(b, 24576);
                                tma_ld3(sb + SM_A0 + 24576, &p.tm_kvl, 0, trow + 128, 12 + 3 * c, b);
                            }
                        }
                        __syncwarp();
                        done |= m;
                    }
                    if (PHASES == 3 && blockIdx.x == 0 && lane == 0) *(volatile unsigned*)&g_epoch = epoch;
                    if (lane == 0) mbar_arrive(bar_addr(sb, B_KVISS));
                }
                mbar_wait_trap(bar_addr(sb, B_A1FREE), 0);
#pragma unroll 1
                for (int j = 0; j < 6; j++) mbar_wait_trap(bar_addr(sb, B_X2C + j), 0);
                if (elect_one()) {
                    const uint32_t b = bar_addr(sb, B_W1X);
                    mbar_expect_tx(b, 49152);
#pragma unroll 1
                    for (int j = 0; j < 6; j++) { int ch = c + (j >> 1); if (ch >= 6) ch -= 6; tma_ld2(sb + SM_A1 + j * 8192, &p.tm_w[4], 256 * c + 128 + 64 * (j & 1), 64 * ch, b); }
                }
                __syncwarp();
            }
        } else if (warp == 11) {
            if (P1 && elect_one()) {
                mbar_wait_trap(bar_addr(sb, B_X1C + c), 0);
                tma_st5(&p.tm_x1s, 64 * c, 0, 0, 0, 4 * k, sb + SM_A1 + c * 8192);
                mbar_wait_trap(bar_addr(sb, B_X1ST), 0);
#pragma unroll 1
                for (int t = 0; t < 4; t++) bulk_s2g(g_part + ((k * 4 + t) * 6 + c) * 16, sb + SM_ML + t * 128, 128);
                bulk_commit(); bulk_wait<0>();
                if (PHASES == 3) signal_cnt(g_cnt + 32 * (k >> 2));
                mbar_arrive(bar_addr(sb, B_X1PUB));
                mbar_wait_trap(bar_addr(sb, B_KVST), 0);
                tma_st5(&p.tm_kvs, 128 * c, 0, 0, 0, 4 * k, sb + SM_STG);
                tma_st5(&p.tm_kvs, 128 * c + 64, 0, 0, 0, 4 * k, sb + SM_STG + 8192);
                bulk_commit(); bulk_wait<0>();
                if (PHASES == 3) { mbar_wait_trap(bar_addr(sb, B_EPOCH), 0); signal_cnt(g_cnt + 128 + 32 * ((c >= 3 ? 2 : 0) + (k >> 3))); }
                mbar_arrive(bar_addr(sb, B_STGFREE));
            }
        }
    } else {
        asm volatile("setmaxnreg.inc.sync.aligned.u32 232;");
        const int wg = warp >> 2, ww = warp & 3;
        const int g = lane >> 2, q4 = lane & 3;
        const int row0 = 16 * ww + g;
        const int lrow = 16 * ww + (lane & 15);
        const uint32_t hi = lane >> 4;
        const uint32_t a128 = lrow * 128 + (((lrow & 7) ^ hi) << 4);
        const uint32_t a64 = lrow * 64 + ((((lrow >> 1) & 3) ^ hi) << 4);
        const bool diag = (q4 == (g >> 1));
        uint8_t* img = g_img + blockIdx.x * 12288;
        asm volatile("" : "+l"(img));
        uint8_t* outp = (uint8_t*)p.out + ((size_t)(k * 64 + 16 * ww + (lane >> 3)) * 384 + 64 * c + (lane & 7) * 8) * 2;
        asm volatile("" : "+l"(outp));
        constexpr uint32_t SQ = P1 ? 15 : 0;
        const uint32_t sp = SQ + (att ? 6 : 0);
        uint32_t nm0 = 0, nm1 = 0; float r0, r1;
        if (P1) {
            mbar_wait(bar_addr(sb, B_X), 0);
            const uint32_t tile = sb + SM_A1;
            if (wg == 0) {
                float acc[64];
                uint32_t sdst[2][3], sbar[2][3];
#pragma unroll
                for (int a = 0; a < 2; a++) {
                    const int un = 2 * c + a, h = (un * 43) >> 7, slot = un - 3 * h;
#pragma unroll
                    for (int d = 0; d < 3; d++) {
                        const int u2 = 3 * h + d;
                        sdst[a][d] = mapa(sb + SM_SC + (u2 & 1) * 3072 + slot * 1024 + row0 * 16, u2 >> 1);
                        sbar[a][d] = mapa(bar_addr(sb, B_SC), u2 >> 1);
                    }
                }
                gemm_rs<128, 1, true>(acc, sb, tile + a128, 0, 0, 0, 1, lane, 2);
#pragma unroll
                for (int a = 0; a < 2; a++) {
                    float s0[4] = {0.f, 0.f, 0.f, 0.f}, s1[4] = {0.f, 0.f, 0.f, 0.f};
#pragma unroll
                    for (int s = 0; s < 2; s++) {
                        const int o = 16 * a + 8 * s;
                        const uint32_t q0 = pack_bf16(acc[o], acc[o + 1]), q1 = pack_bf16(acc[o + 2], acc[o + 3]);
                        const uint32_t q2 = pack_bf16(acc[o + 4], acc[o + 5]), q3 = pack_bf16(acc[o + 6], acc[o + 7]);
                        mma16816(s0, q0, q1, q2, q3, pack_bf16(acc[32 + o], acc[33 + o]), pack_bf16(acc[36 + o], acc[37 + o]));
                        mma16816(s1, q0, q1, q2, q3, pack_bf16(acc[34 + o], acc[35 + o]), pack_bf16(acc[38 + o], acc[39 + o]));
                    }
                    if (diag) {
#pragma unroll
                        for (int d = 0; d < 3; d++) {
                            st_async_v4(sdst[a][d], __float_as_uint(s0[0]), __float_as_uint(s0[1]), __float_as_uint(s1[0]), __float_as_uint(s1[1]), sbar[a][d]);
                            st_async_v4(sdst[a][d] + 128, __float_as_uint(s0[2]), __float_as_uint(s0[3]), __float_as_uint(s1[2]), __float_as_uint(s1[3]), sbar[a][d]);
                        }
                    }
                }
            } else {
                {
                    float s0 = 0.f, q0 = 0.f, s1 = 0.f, q1 = 0.f;
                    uint32_t a = tile + a128;
#pragma unroll 1
                    for (int j = 0; j < 12; j++) {
                        uint32_t t[8];
                        ldsm4(a, t[0], t[1], t[2], t[3]);
                        ldsm4(a ^ 32, t[4], t[5], t[6], t[7]);
                        a = (j & 1) ? (a ^ 64) + 8192 : (a ^ 64);
#pragma unroll
                        for (int i = 0; i < 8; i++) {
                            const float lo = bf_lo(t[i]), hi2 = bf_hi(t[i]);
                            if (i & 1) { s1 += lo + hi2; q1 = fmaf(lo, lo, fmaf(hi2, hi2, q1)); } else { s0 += lo + hi2; q0 = fmaf(lo, lo, fmaf(hi2, hi2, q0)); }
                        }
                    }
                    s0 += __shfl_xor_sync(0xffffffffu, s0, 1); q0 += __shfl_xor_sync(0xffffffffu, q0, 1);
                    s1 += __shfl_xor_sync(0xffffffffu, s1, 1); q1 += __shfl_xor_sync(0xffffffffu, q1, 1);
                    s0 += __shfl_xor_sync(0xffffffffu, s0, 2); q0 += __shfl_xor_sync(0xffffffffu, q0, 2);
                    s1 += __shfl_xor_sync(0xffffffffu, s1, 2); q1 += __shfl_xor_sync(0xffffffffu, q1, 2);
                    finish_stats(s0, q0, s1, q1, nm0, nm1, r0, r1);
                }
                asm volatile("barrier.cluster.wait.aligned;" ::: "memory");
                float acc[32];
                gemm_rs<64, 2, false, true, false, true>(acc, sb, tile + a128, nm0, nm1, SM_A0, B_VW, lane, -1, false, 2);
                if (lane < CS) mbar_arrive_remote(mapa(bar_addr(sb, B_VFREE), lane));
                uint32_t vb[16];
#pragma unroll
                for (int j = 0; j < 8; j++) {
                    vb[2 * j] = movm(pack_bf16(acc[4 * j], acc[4 * j + 1]));
                    vb[2 * j + 1] = movm(pack_bf16(acc[4 * j + 2], acc[4 * j + 3]));
                }
                const float p0 = __shfl_xor_sync(0xffffffffu, r0, 4), p1 = __shfl_xor_sync(0xffffffffu, r1, 4);
                const bool odd = g & 1;
                const float rk0 = odd ? p0 : r0, rk1 = odd ? r0 : p0, rk2 = odd ? p1 : r1, rk3 = odd ? r1 : p1;
                mbar_wait_cl(bar_addr(sb, B_SC), 0);
                uint32_t o[16], pa[2][4];
#pragma unroll
                for (int a = 0; a < 2; a++)
#pragma unroll
                    for (int i = 0; i < 2; i++) {
                        const uint32_t ad = SM_SC + a * 3072 + (row0 + 8 * i) * 16;
                        const float4 x0 = sm_at<float4>(ad), x1 = sm_at<float4>(ad + 1024), x2 = sm_at<float4>(ad + 2048);
                        const float f = (i ? r1 : r0) * SL2;
                        const float s0 = (x0.x + x1.x + x2.x) * (f * rk0), s1 = (x0.y + x1.y + x2.y) * (f * rk1);
                        const float s2 = (x0.z + x1.z + x2.z) * (f * rk2), s3 = (x0.w + x1.w + x2.w) * (f * rk3);
                        const float m = fmaxf(fmaxf(s0, s1), fmaxf(s2, s3));
                        const float e0 = ex2(s0 - m), e1 = ex2(s1 - m), e2 = ex2(s2 - m), e3 = ex2(s3 - m);
                        float inv; asm("rcp.approx.ftz.f32 %0, %1;" : "=f"(inv) : "f"((e0 + e1) + (e2 + e3)));
                        inv = diag ? inv : 0.f;
                        pa[a][i] = pack_bf16(e0 * (inv * rk0), e1 * (inv * rk1));
                        pa[a][2 + i] = pack_bf16(e2 * (inv * rk2), e3 * (inv * rk3));
                    }
#pragma unroll
                for (int j = 0; j < 8; j++) {
                    float d[4] = {0.f, 0.f, 0.f, 0.f};
                    mma16816(d, pa[j >> 2][0], pa[j >> 2][1], pa[j >> 2][2], pa[j >> 2][3], vb[2 * j], vb[2 * j + 1]);
                    o[2 * j] = pack_bf16(d[0], d[1]); o[2 * j + 1] = pack_bf16(d[2], d[3]);
                }
#pragma unroll
                for (int jj = 0; jj < 4; jj++)
                    stsm4(sb + SM_STG + (a128 ^ (jj << 5)), o[4 * jj], o[4 * jj + 1], o[4 * jj + 2], o[4 * jj + 3]);
                fence_async_smem();
                __syncwarp();
                const bool leader = elect_one();
                uint8_t* gi = img + IMG_OT + ww * 2048;
                if (leader) { bulk_s2g(gi, sb + SM_STG + ww * 2048, 2048); bulk_commit(); }
                mbar_wait(bar_addr(sb, B_VFREE), 0);
#pragma unroll
                for (int jj = 0; jj < 4; jj++)
                    stsm4(sb + SM_A0 + c * 8192 + (a128 ^ (jj << 5)), o[4 * jj], o[4 * jj + 1], o[4 * jj + 2], o[4 * jj + 3]);
                fence_async_smem();
                __syncwarp();
                if (leader) {
                    mbar_arrive(bar_addr(sb, B_OTC + c));
                    bulk_wait<0>();
                    bulk_g2s_mc(sb + SM_A0 + c * 8192 + ww * 2048, gi, 2048, bar_addr(sb, B_OTC + c), (uint16_t)(0x3F & ~(1 << c)));
                }
                __syncwarp();
                proj_block<0>(sb, 6, c, k, lane, ww, a128, img);
            }
            if (wg == 0) {
                mbar_wait_cl(bar_addr(sb, B_ST2), 0);
                combine_stats<512, 64>(SM_ST + row0 * 8, nm0, nm1, r0, r1);
                float acc[64];
                gemm_rs<128, 1, false, false, false, false, B_X1C>(acc, sb, sb + SM_A1 + a128, nm0, nm1, 9, 1, lane, -1, false, -1, c);
#pragma unroll
                for (int jj = 0; jj < 8; jj++)
                    stsm4(sb + SM_STG + (jj >> 2) * 8192 + (a128 ^ ((jj & 3) << 5)),
                          pack_bf16(acc[8 * jj] * r0, acc[8 * jj + 1] * r0), pack_bf16(acc[8 * jj + 2] * r1, acc[8 * jj + 3] * r1),
                          pack_bf16(acc[8 * jj + 4] * r0, acc[8 * jj + 5] * r0), pack_bf16(acc[8 * jj + 6] * r1, acc[8 * jj + 7] * r1));
                fence_async_smem();
                __syncwarp();
                if (lane == 0) mbar_arrive(bar_addr(sb, B_KVST));
            }
        } else {
            asm volatile("barrier.cluster.wait.aligned;" ::: "memory");
        }
        if (P2) {
            if (!att && lane < 4) { if (wg == 0) { mbar_arrive_remote(mapa(bar_addr(sb, B_KFREE), lane)); mbar_arrive_remote(mapa(bar_addr(sb, B_KFREE), lane)); } }
            mbar_wait(bar_addr(sb, B_X1P), 0);
            if (att) {
                if (wg == 0) {
                    float acc[48];
                    combine_stats<128, 64>(SM_SC + ww * 768 + g * 8, nm0, nm1, r0, r1);
                    gemm_rs<96, 1, false, false, false, false, B_X1PC>(acc, sb, sb + SM_A0 + a128, nm0, nm1, SQ, 1, lane, -1, false, -1, 0);
                    if (lane == 0) mbar_arrive(bar_addr(sb, B_QDONE));
                    if (P1) mbar_wait(bar_addr(sb, B_STGFREE), 0);
#pragma unroll
                    for (int jj = 0; jj < 6; jj++)
                        stsm4(sb + SM_STG + (jj >> 1) * 4096 + (a64 ^ ((jj & 1) << 5)),
                              pack_bf16(acc[8 * jj] * r0, acc[8 * jj + 1] * r0), pack_bf16(acc[8 * jj + 2] * r1, acc[8 * jj + 3] * r1),
                              pack_bf16(acc[8 * jj + 4] * r0, acc[8 * jj + 5] * r0), pack_bf16(acc[8 * jj + 6] * r1, acc[8 * jj + 7] * r1));
                    fence_async_smem();
                }
                bar_sync(1, 256);
                float s[64];
                {
                    const uint64_t da = mkd(sb + SM_STG, 16, DHI_64), db = mkd(sb + SM_A1 + wg * 24576, 16, DHI_64);
#pragma unroll
                    for (int blk = 0; blk < 3; blk++) {
                        mbar_wait(bar_addr(sb, wg ? B_K1 : B_K0 + blk), 0);
                        wg_fence();
                        wgmma_ss_n128_bn(s, da + blk * 256, db + blk * 512, blk != 0);
                        wgmma_ss_n128_bn(s, da + blk * 256 + 2, db + blk * 512 + 2, 1);
                        wg_commit();
                    }
                    wg_wait<0>();
                    pin_f(s);
                }
                if (lane < 4) mbar_arrive_remote(mapa(bar_addr(sb, B_KFREE), lane));
                float m0 = fmaxf(s[0], s[1]), m1 = fmaxf(s[2], s[3]);
#pragma unroll
                for (int j = 1; j < 16; j++) { m0 = fmaxf(m0, fmaxf(s[4 * j], s[4 * j + 1])); m1 = fmaxf(m1, fmaxf(s[4 * j + 2], s[4 * j + 3])); }
                m0 = fmaxf(m0, __shfl_xor_sync(0xffffffffu, m0, 1)); m1 = fmaxf(m1, __shfl_xor_sync(0xffffffffu, m1, 1));
                m0 = fmaxf(m0, __shfl_xor_sync(0xffffffffu, m0, 2)); m1 = fmaxf(m1, __shfl_xor_sync(0xffffffffu, m1, 2));
                m0 *= SL2; m1 *= SL2;
                float l0 = 0.f, l1 = 0.f;
                uint32_t pa[32];
#pragma unroll
                for (int j = 0; j < 16; j++) {
                    const float e0 = ex2v(fmaf(s[4 * j], SL2, -m0)), e1 = ex2v(fmaf(s[4 * j + 1], SL2, -m0));
                    const float e2 = ex2v(fmaf(s[4 * j + 2], SL2, -m1)), e3 = ex2v(fmaf(s[4 * j + 3], SL2, -m1));
                    l0 += e0 + e1; l1 += e2 + e3;
                    pa[2 * j] = pack_bf16(e0, e1); pa[2 * j + 1] = pack_bf16(e2, e3);
                }
                float o[48];
                mbar_wait(bar_addr(sb, B_V0 + wg), 0);
                {
                    const uint64_t db = mkd(sb + SM_A0 + wg * 24576, 8192, DHI_64);
                    wg_fence();
#pragma unroll
                    for (int ks = 0; ks < 8; ks++)
                        wgmma_rs_n96(o, pa[4 * ks], pa[4 * ks + 1], pa[4 * ks + 2], pa[4 * ks + 3], db + ks * 64, ks != 0);
                    wg_commit();
                }
                l0 += __shfl_xor_sync(0xffffffffu, l0, 1); l1 += __shfl_xor_sync(0xffffffffu, l1, 1);
                l0 += __shfl_xor_sync(0xffffffffu, l0, 2); l1 += __shfl_xor_sync(0xffffffffu, l1, 2);
                if (q4 == 0) { sm_at<float2>(SM_ML + wg * 512 + row0 * 8) = make_float2(m0, l0); sm_at<float2>(SM_ML + wg * 512 + row0 * 8 + 64) = make_float2(m1, l1); }
                wg_wait<0>();
                pin_r(pa); pin_f(o);
                bar_sync(wg ? 8 : 3, 128);
                const uint32_t t16 = (tid & 127) * 16;
                const uint32_t scr_own = SM_A0 + wg * 24576 + t16, scr_oth = SM_A0 + (wg ^ 1) * 24576 + t16;
                if (wg == 0) {
#pragma unroll
                    for (int v = 0; v < 6; v++) sm_at<float4>(scr_own + v * 2048) = make_float4(o[24 + 4 * v], o[25 + 4 * v], o[26 + 4 * v], o[27 + 4 * v]);
                } else {
#pragma unroll
                    for (int v = 0; v < 6; v++) sm_at<float4>(scr_own + v * 2048) = make_float4(o[4 * v], o[4 * v + 1], o[4 * v + 2], o[4 * v + 3]);
                }
                bar_sync(1, 256);
                float4 y[6];
#pragma unroll
                for (int v = 0; v < 6; v++) y[v] = sm_at<float4>(scr_oth + v * 2048);
                const float2 x0 = sm_at<float2>(SM_ML + (wg ^ 1) * 512 + row0 * 8), x1 = sm_at<float2>(SM_ML + (wg ^ 1) * 512 + row0 * 8 + 64);
                const float mm0 = fmaxf(m0, x0.x), mm1 = fmaxf(m1, x1.x);
                float a0 = ex2(m0 - mm0), b0 = ex2(x0.x - mm0), a1 = ex2(m1 - mm1), b1 = ex2(x1.x - mm1);
                float i0, i1;
                asm("rcp.approx.ftz.f32 %0, %1;" : "=f"(i0) : "f"(a0 * l0 + b0 * x0.y));
                asm("rcp.approx.ftz.f32 %0, %1;" : "=f"(i1) : "f"(a1 * l1 + b1 * x1.y));
                a0 *= i0; b0 *= i0; a1 *= i1; b1 *= i1;
#define COMBINE(O)                                                                                                                       \
                _Pragma("unroll") for (int jj = 0; jj < 3; jj++) {                                                                       \
                    const float4 ya = y[2 * jj], yb = y[2 * jj + 1];                                                                     \
                    const int u = (O) / 8 + jj;                                                                                          \
                    const float* w = &o[(O) + 8 * jj];                                                                                   \
                    const uint32_t p0 = pack_bf16(a0 * w[0] + b0 * ya.x, a0 * w[1] + b0 * ya.y), p1 = pack_bf16(a1 * w[2] + b1 * ya.z, a1 * w[3] + b1 * ya.w); \
                    const uint32_t p2 = pack_bf16(a0 * w[4] + b0 * yb.x, a0 * w[5] + b0 * yb.y), p3 = pack_bf16(a1 * w[6] + b1 * yb.z, a1 * w[7] + b1 * yb.w); \
                    const uint32_t o2 = (u >> 1) * 4096 + (a64 ^ ((u & 1) << 5));                                                        \
                    stsm4(sb + SM_STG + o2, p0, p1, p2, p3);                                                                             \
                    stsm4(sb + SM_A1 + c * 12288 + o2, p0, p1, p2, p3);                                 \
                }
                if (wg == 0) { COMBINE(0) } else { COMBINE(24) }
#undef COMBINE
                fence_async_smem();
                bar_sync(1, 256);
                if (warp < 3 && elect_one()) {
                    uint8_t* gi = img + IMG_OS + warp * 4096;
                    bulk_s2g(gi, sb + SM_STG + warp * 4096, 4096); bulk_commit();
                    if (warp == 0) mbar_arrive(bar_addr(sb, B_OSH + c));
                    mbar_wait(bar_addr(sb, B_KFREE), 0);
                    bulk_wait<0>();
                    bulk_g2s_mc(sb + SM_A1 + c * 12288 + warp * 4096, gi, 4096, bar_addr(sb, B_OSH + c), (uint16_t)(0x3F & ~(1 << c)));
                }
                __syncwarp();
            }
            if (wg == 1) proj_block<1>(sb, sp, c, k, lane, ww, a128, img);
            mbar_wait_cl(bar_addr(sb, B_ST3), 0);
            combine_stats<512, 64>(SM_ST + row0 * 8, nm0, nm1, r0, r1);
            uint32_t hp[32];
            {
                float h[64];
                gemm_rs<128, 1, false, false, true, false, B_X2C>(h, sb, sb + SM_A0 + a128, nm0, nm1, sp + 3 + 6 * wg, 1, lane, 4 + wg, wg == 1, wg == 1 ? 4 : -1, c);
                if (wg == 1 && lane < 5) { int d = c + 1 + lane; if (d >= 6) d -= 6; mbar_arrive_remote(mapa(bar_addr(sb, B_LAND), d)); }
                const float k0 = 0.7978845608028654f, k1 = 0.7978845608028654f * 0.044715f;
                const float A0 = k0 * r0, B0 = k1 * r0 * r0 * r0, H0 = 0.5f * r0, A1 = k0 * r1, B1 = k1 * r1 * r1 * r1, H1 = 0.5f * r1;
                const uint32_t dst = sb + (wg ? SM_A1 : SM_STG);
#pragma unroll
                for (int jj = 0; jj < 8; jj++) {
                    hp[4 * jj] = pack_bf16(gelu_f(h[8 * jj], A0, B0, H0), gelu_f(h[8 * jj + 1], A0, B0, H0));
                    hp[4 * jj + 1] = pack_bf16(gelu_f(h[8 * jj + 2], A1, B1, H1), gelu_f(h[8 * jj + 3], A1, B1, H1));
                    hp[4 * jj + 2] = pack_bf16(gelu_f(h[8 * jj + 4], A0, B0, H0), gelu_f(h[8 * jj + 5], A0, B0, H0));
                    hp[4 * jj + 3] = pack_bf16(gelu_f(h[8 * jj + 6], A1, B1, H1), gelu_f(h[8 * jj + 7], A1, B1, H1));
                    stsm4(dst + (jj >> 2) * 8192 + (a128 ^ ((jj & 3) << 5)), hp[4 * jj], hp[4 * jj + 1], hp[4 * jj + 2], hp[4 * jj + 3]);
                }
            }
            if (wg == 0) { bar_arrive(6, 256); bar_sync(5, 256); }
            else bar_arrive(7, 256);
            float acc2[3][32];
            const uint32_t t16 = (tid & 127) * 16;
            {
                const RingPos r1p = ring_pos(sp + 12 + 3 * wg);
                {
                    const uint64_t db = mkd(sb + SM_RING + r1p.slot * SLOT, 8192, DHI_B);
#pragma unroll
                    for (int l = 0; l < 3; l++) {
                        mbar_wait(sb + SM_BAR + (B_FULL + r1p.slot + l) * 8, r1p.par);
                        wg_fence();
#pragma unroll
                        for (int ks = 0; ks < 8; ks++) wgmma_rs_n64(acc2[l], hp[4 * ks], hp[4 * ks + 1], hp[4 * ks + 2], hp[4 * ks + 3], db + l * 1024 + ks * 128, ks != 0);
                        wg_commit();
                        if (l) { wg_wait<1>(); ring_release(sb, r1p.slot + l - 1, lane); }
                    }
                    bar_arrive(11 + wg, 256);
                    wg_wait<0>();
                    pin_r(hp);
                    ring_release(sb, r1p.slot + 2, lane);
                }
                bar_sync(wg == 0 ? 7 : 6, 256);
                uint32_t ho[32];
                const uint32_t src = sb + (wg ? SM_STG : SM_A1);
#pragma unroll
                for (int jj = 0; jj < 8; jj++) ldsm4(src + (jj >> 2) * 8192 + (a128 ^ ((jj & 3) << 5)), ho[4 * jj], ho[4 * jj + 1], ho[4 * jj + 2], ho[4 * jj + 3]);
                RingPos rp = ring_pos(sp + 18 + wg), rr = rp;
#define G2_ISSUE(L)                                                                                                                   \
                {                                                                                                                       \
                    ring_wait(sb, rp);                                                                                                  \
                    const uint64_t db = mkd(sb + SM_RING + rp.slot * SLOT, 8192, DHI_B);                                                \
                    wg_fence();                                                                                                         \
                    _Pragma("unroll") for (int ks = 0; ks < 8; ks++)                                                                    \
                        wgmma_rs_n64(acc2[L], ho[4 * ks], ho[4 * ks + 1], ho[4 * ks + 2], ho[4 * ks + 3], db + ks * 128, 1);            \
                    wg_commit();                                                                                                        \
                    ring_adv(rp, 2);                                                                                                    \
                }
#define G2_SEND(L)                                                                                                                    \
                {                                                                                                                       \
                    pin_f(acc2[L]);                                                                                                     \
                    ring_release(sb, rr.slot, lane);                                                                                    \
                    ring_adv(rr, 2);                                                                                                    \
                    const int kk = 2 * L + wg;                                                                                          \
                    if (kk < 5) {                                                                                                       \
                        int d = c + 1 + kk; if (d >= 6) d -= 6;                                                                         \
                        const uint32_t dst = mapa(sb + SM_A0 + c * 8192 + t16, d), rb = mapa(bar_addr(sb, B_PART + kk), d);                  \
                        _Pragma("unroll") for (int v = 0; v < 4; v++) {                                                                 \
                            const float* z = &acc2[L][8 * v];                                                                           \
                            st_async_v4(dst + v * 2048, pack_bf16(z[0], z[1]), pack_bf16(z[2], z[3]), pack_bf16(z[4], z[5]), pack_bf16(z[6], z[7]), rb); \
                        }                                                                                                               \
                    }                                                                                                                   \
                }
                if (wg == 1) bar_sync(11, 256);
                G2_ISSUE(0) G2_ISSUE(1)
                mbar_wait(bar_addr(sb, B_LAND), 0);
                wg_wait<1>(); G2_SEND(0)
                if (wg == 0) bar_sync(12, 256);
                G2_ISSUE(2)
                wg_wait<1>(); G2_SEND(1)
                wg_wait<0>(); G2_SEND(2)
                pin_r(ho);
#undef G2_ISSUE
#undef G2_SEND
            }
            if (wg == 1) {
                const uint32_t idf = (2 * q4 == g ? 0x3F80u : 0u) | (2 * q4 + 1 == g ? 0x3F800000u : 0u);
                uint32_t r[16];
#pragma unroll
                for (int jj = 0; jj < 4; jj++) ldsm4(sb + SM_RES + (a128 ^ (jj << 5)), r[4 * jj], r[4 * jj + 1], r[4 * jj + 2], r[4 * jj + 3]);
#pragma unroll
                for (int kk = 0; kk < 5; kk++) {
                    int src = c + 5 - kk; if (src >= 6) src -= 6;
                    mbar_wait_cl(bar_addr(sb, B_PART + kk), 0);
#pragma unroll
                    for (int v = 0; v < 4; v++) {
                        const uint4 y = sm_at<uint4>(SM_A0 + src * 8192 + v * 2048 + t16);
                        mma16816p(&acc2[2][8 * v], y.x, y.y, y.z, y.w, idf, 0u);
                        mma16816p(&acc2[2][4 + 8 * v], y.x, y.y, y.z, y.w, 0u, idf);
                    }
                }
#pragma unroll
                for (int jj = 0; jj < 4; jj++) {
#pragma unroll
                    for (int i = 0; i < 4; i++) r[4 * jj + i] = hadd2_bf(r[4 * jj + i], pack_bf16(acc2[2][8 * jj + 2 * i], acc2[2][8 * jj + 2 * i + 1]));
                    stsm4(sb + SM_RES + (a128 ^ (jj << 5)), r[4 * jj], r[4 * jj + 1], r[4 * jj + 2], r[4 * jj + 3]);
                }
                __syncwarp();
                uint8_t* orow = outp;
#pragma unroll
                for (int i = 0; i < 4; i++) {
                    const int rr2 = 16 * ww + 4 * i + (lane >> 3);
                    const uint4 v = sm_at<uint4>(SM_RES + rr2 * 128 + (((lane & 7) ^ (rr2 & 7)) << 4));
                    *reinterpret_cast<uint4*>(orow + (size_t)i * 4 * 768) = v;
                }
            }
        }
        if (lane == 0) mbar_arrive(bar_addr(sb, B_DONE));
    }
}

}

typedef CUresult (*EncodeFn)(CUtensorMap*, CUtensorMapDataType, cuuint32_t, void*, const cuuint64_t*, const cuuint64_t*, const cuuint32_t*,
                             const cuuint32_t*, CUtensorMapInterleave, CUtensorMapSwizzle, CUtensorMapL2promotion, CUtensorMapFloatOOBfill);

static void encode_map(EncodeFn enc, CUtensorMap* tm, const void* base, int rank, const cuuint64_t* dims, const cuuint64_t* strides,
                       const cuuint32_t* box, CUtensorMapSwizzle swz) {
    cuuint32_t es[5] = {1, 1, 1, 1, 1};
    enc(tm, CU_TENSOR_MAP_DATA_TYPE_BFLOAT16, (cuuint32_t)rank, const_cast<void*>(base), dims, strides, box, es,
        CU_TENSOR_MAP_INTERLEAVE_NONE, swz, CU_TENSOR_MAP_L2_PROMOTION_NONE, CU_TENSOR_MAP_FLOAT_OOB_FILL_NONE);
}

extern "C" void kernel_launch(void* const* d_in, const int* in_sizes, int n_in, void* d_out, int out_size) {
    (void)in_sizes; (void)n_in; (void)out_size;
    static Params prm;
    static const void* cached[8] = {nullptr};
    static int mode = -1;
    bool same = (mode >= 0) && cached[7] == d_out;
    for (int i = 0; i < 7 && same; i++) same = cached[i] == d_in[i];
    if (!same) {
        void* fn = nullptr; cudaDriverEntryPointQueryResult qr;
        cudaGetDriverEntryPoint("cuTensorMapEncodeTiled", &fn, cudaEnableDefault, &qr);
        EncodeFn enc = (EncodeFn)fn;
        void *a_x1, *a_kv;
        cudaGetSymbolAddress(&a_x1, g_x1); cudaGetSymbolAddress(&a_kv, g_kv);
        {
            cuuint64_t d[5] = {384, 2, 4, 2, 64};
            cuuint64_t s[4] = {256ull * 768, 768, 2ull * 256 * 768, 4ull * 768};
            cuuint32_t b4[5] = {64, 2, 4, 2, 4};
            encode_map(enc, &prm.tm_x, d_in[0], 5, d, s, b4, CU_TENSOR_MAP_SWIZZLE_128B);
            encode_map(enc, &prm.tm_x1s, a_x1, 5, d, s, b4, CU_TENSOR_MAP_SWIZZLE_128B);
            cuuint64_t d2[5] = {768, 2, 4, 2, 64};
            cuuint64_t s2[4] = {256ull * 1536, 1536, 2ull * 256 * 1536, 4ull * 1536};
            encode_map(enc, &prm.tm_kvs, a_kv, 5, d2, s2, b4, CU_TENSOR_MAP_SWIZZLE_128B);
        }
        {
            cuuint64_t d[2] = {384, 1024}; cuuint64_t s[1] = {768};
            cuuint32_t b[2] = {64, 64};
            encode_map(enc, &prm.tm_x1l, a_x1, 2, d, s, b, CU_TENSOR_MAP_SWIZZLE_128B);
            prm.out = d_out;
        }
        {
            cuuint64_t d[3] = {32, 1024, 24}; cuuint64_t s[2] = {1536, 64};
            cuuint32_t b[3] = {32, 128, 3};
            encode_map(enc, &prm.tm_kvl, a_kv, 3, d, s, b, CU_TENSOR_MAP_SWIZZLE_64B);
            cuuint32_t b1[3] = {32, 128, 1};
            encode_map(enc, &prm.tm_kvl1, a_kv, 3, d, s, b1, CU_TENSOR_MAP_SWIZZLE_64B);
        }
        const int wn[6] = {1152, 384, 1152, 384, 1536, 384}, wk[6] = {384, 384, 384, 384, 384, 1536};
        for (int i = 0; i < 6; i++) {
            cuuint64_t d[2] = {(cuuint64_t)wn[i], (cuuint64_t)wk[i]}; cuuint64_t s[1] = {(cuuint64_t)wn[i] * 2};
            cuuint32_t b[2] = {64, 64};
            encode_map(enc, &prm.tm_w[i], d_in[1 + i], 2, d, s, b, CU_TENSOR_MAP_SWIZZLE_128B);
            prm.wptr[i] = d_in[1 + i];
        }
        {
            cuuint64_t d[3] = {32, 384, 36}; cuuint64_t s[2] = {2304, 64};
            cuuint32_t b[3] = {32, 64, 3};
            encode_map(enc, &prm.tm_w[6], d_in[3], 3, d, s, b, CU_TENSOR_MAP_SWIZZLE_64B);
        }
        for (int c = 0; c < 6; c++) {
            int n = 0;
            for (int u = 0; u < 48; u++) {
                if (c >= 4 && u >= 15 && u < 21) continue;
                if (u >= 30 && u < 33) continue;
                int m, x0, y0, mode, gate = 0;
                if (u < 6) { m = 0; x0 = 64 * c; y0 = 64 * u; mode = 0; }
                else if (u < 9) { m = 1; x0 = 64 * c; y0 = 64 * ((c + 2 * (u - 6)) % 6); mode = 3; }
                else if (u < 15) { m = 2; x0 = 384 + 128 * c; y0 = 64 * ((c + u - 9) % 6); mode = 2; gate = (u == 9 || u == 10) ? 1 : 0; }
                else if (u < 21) { m = 6; x0 = 3 * c; y0 = 64 * (u - 15); mode = 2; gate = (u == 15 || u == 16) ? 3 : 0; }
                else if (u < 24) { m = 3; x0 = 64 * c; y0 = 64 * (((c < 4 ? (3 * c + 1) / 2 : 0) + 2 * (u - 21)) % 6); mode = 3; gate = (c < 4 && (u == 21 || u == 22)) ? 2 : 0; }
                else if (u < 36) { const int hh = (u - 24) / 6, j = (u - 24) % 6; m = 4; x0 = 256 * c + 128 * hh; y0 = 64 * ((c + j) % 6); mode = 2; }
                else {
                    const int pass = (u - 36) / 6, i = (u - 36) % 6;
                    const int kk = pass ? i : (i < 3 ? 2 * i : 2 * (i - 3) + 1);
                    const int hh = pass ? 1 - (kk & 1) : (kk & 1);
                    m = 5; x0 = 64 * ((c + 1 + kk) % 6); y0 = 256 * c + 128 * hh; mode = 1;
                }
                prm.stage[c][n++] = (uint32_t)x0 | ((uint32_t)y0 << 11) | ((uint32_t)m << 22) | ((uint32_t)mode << 25) | ((uint32_t)gate << 27);
            }
        }
        cudaFuncSetAttribute(fused_kernel<3>, cudaFuncAttributeMaxDynamicSharedMemorySize, SM_TOTAL);
        cudaFuncSetAttribute(fused_kernel<1>, cudaFuncAttributeMaxDynamicSharedMemorySize, SM_TOTAL);
        cudaFuncSetAttribute(fused_kernel<2>, cudaFuncAttributeMaxDynamicSharedMemorySize, SM_TOTAL);
        cudaLaunchConfig_t cfg = {};
        cfg.gridDim = dim3(NCL * CS); cfg.blockDim = dim3(NTHREADS); cfg.dynamicSmemBytes = SM_TOTAL;
        cudaLaunchAttribute at[1];
        at[0].id = cudaLaunchAttributeClusterDimension; at[0].val.clusterDim.x = CS; at[0].val.clusterDim.y = 1; at[0].val.clusterDim.z = 1;
        cfg.attrs = at; cfg.numAttrs = 1;
        int ncl = 0;
        cudaOccupancyMaxActiveClusters(&ncl, fused_kernel<3>, &cfg);
        mode = (ncl >= NCL) ? 3 : 0;
        for (int i = 0; i < 7; i++) cached[i] = d_in[i];
        cached[7] = d_out;
    }
    cudaLaunchConfig_t cfg = {};
    cfg.gridDim = dim3(NCL * CS); cfg.blockDim = dim3(NTHREADS); cfg.dynamicSmemBytes = SM_TOTAL; cfg.stream = cudaStreamPerThread;
    cudaLaunchAttribute at[1];
    at[0].id = cudaLaunchAttributeClusterDimension; at[0].val.clusterDim.x = CS; at[0].val.clusterDim.y = 1; at[0].val.clusterDim.z = 1;
    cfg.attrs = at; cfg.numAttrs = 1;
    if (mode == 3) {
        cudaLaunchKernelEx(&cfg, fused_kernel<3>, prm);
    } else {
        cudaLaunchKernelEx(&cfg, fused_kernel<1>, prm);
        cudaLaunchKernelEx(&cfg, fused_kernel<2>, prm);
    }
}
```
